```python
import torch

def _softmax(x, axis=-1):
    return torch.softmax(x, dim=axis)
def _gelu(x):
    return torch.nn.functional.gelu(x, approximate="tanh")
def _silu(x):
    return torch.nn.functional.silu(x)
def _sigmoid(x):
    return torch.sigmoid(x)
def _layernorm(x, axis=-1, eps=1e-5):
    m = x.mean(dim=axis, keepdim=True)
    v = x.var(dim=axis, keepdim=True, unbiased=False)
    return (x - m) / torch.sqrt(v + eps)
def _scatter_add(tgt, idx, src, axis=0):
    return tgt.clone().index_add_(axis, idx, src)
def _segment_sum(src, seg, n):
    out = torch.zeros((n,) + src.shape[1:], dtype=src.dtype)
    return out.index_add_(0, seg, src)
def _pad(x, pw):
    flat = tuple(v for pair in reversed(pw) for v in pair)
    return torch.nn.functional.pad(x, flat)

kernel_name = 'sequential_preLN__sliding_local_dilated__glu_gated_geglu__prompt'

def setup_inputs():

    _w = (lambda a: (lambda t: t.to(torch.bfloat16) if t.is_floating_point() else t)(torch.as_tensor(a)))
    def _A_setup():
        B, S, D = 1, 2048, 1024
        return {
            "x": _w((lambda *s: torch.randn(*s, dtype=torch.bfloat16) * 0.05)(B, S, D)),
            "wqkv": _w((lambda *s: torch.randn(*s, dtype=torch.bfloat16) * 0.05)(D, 3 * D)),
            "wo": _w((lambda *s: torch.randn(*s, dtype=torch.bfloat16) * 0.05)(D, D)),
        }
    _A_in = _A_setup()

    def _B_setup():
        B, S, Dm, Df = 1, 2048, 1024, 3584
        return {
            "x": _w((lambda *s: torch.randn(*s, dtype=torch.bfloat16) * 0.05)(B, S, Dm)),
            "w_gate": _w((lambda *s: torch.randn(*s, dtype=torch.bfloat16) * 0.8)(Dm, Df) * (Dm ** -0.5)),
            "w_up": _w((lambda *s: torch.randn(*s, dtype=torch.bfloat16) * 0.8)(Dm, Df) * (Dm ** -0.5)),
            "w_down": _w((lambda *s: torch.randn(*s, dtype=torch.bfloat16) * 0.8)(Df, Dm) * (Df ** -0.5)),
        }
    _B_in = _B_setup()

    return {
        "A_x": _A_in["x"],
        "A_wqkv": _A_in["wqkv"],
        "A_wo": _A_in["wo"],
        "B_x": _B_in["x"],
        "B_w_gate": _B_in["w_gate"],
        "B_w_up": _B_in["w_up"],
        "B_w_down": _B_in["w_down"],
    }

def reference(A_x, A_wqkv, A_wo, B_x, B_w_gate, B_w_up, B_w_down):
    def _A_ref(x, wqkv, wo):
        B, S, D = x.shape
        H = 32; Dh = D // H
        W, dil = 8, 2
        qkv = (lambda x, *d: x.permute(*d))((x @ wqkv).reshape(B, S, 3, H, Dh), 2, 0, 3, 1, 4)
        q, k, v = qkv[0], qkv[1], qkv[2]
        scale = Dh ** -0.5
        pos = torch.arange(S)
        off = torch.arange(W) * dil
        idx = pos[:, None] - off[None, :]
        mask = idx >= 0
        idx_c = torch.where(mask, idx, 0).reshape(-1)
        kg = k[:, :, idx_c, :].reshape(B, H, S, W, Dh)
        vg = v[:, :, idx_c, :].reshape(B, H, S, W, Dh)
        logits = torch.einsum("bhsd,bhswd->bhsw", q, kg) * scale
        logits = torch.where(mask[None, None, :, :], logits, -1e9)
        attn = _softmax(logits, axis=-1)
        o = torch.einsum("bhsw,bhswd->bhsd", attn, vg)
        return (lambda x, *d: x.permute(*d))(o, 0, 2, 1, 3).reshape(B, S, D) @ wo

    def _B_ref(x, w_gate, w_up, w_down):
        g = torch.einsum("bsd,df->bsf", x, w_gate)
        u = torch.einsum("bsd,df->bsf", x, w_up)
        h = _gelu(g) * u
        return torch.einsum("bsf,fd->bsd", h, w_down)

    x = A_x
    h = x + _A_ref(_layernorm(x, axis=-1), A_wqkv, A_wo)
    h2 = h + _B_ref(_layernorm(h, axis=-1), B_w_gate, B_w_up, B_w_down)
    return h2
```

```cpp
#include <cuda_runtime.h>
#include <cuda_bf16.h>
#include <cuda.h>
#include <stdint.h>
#include <string.h>

template <int N>
__device__ __forceinline__ void wgmma128(float (&d)[N], uint64_t da, uint64_t db) {
  asm volatile("wgmma.mma_async.sync.aligned.m64n128k16.f32.bf16.bf16 "
    "{%0, %1, %2, %3, %4, %5, %6, %7, %8, %9, %10, %11, %12, %13, %14, %15, %16, %17, %18, %19, %20, %21, %22, %23, %24, %25, %26, %27, %28, %29, %30, %31, %32, %33, %34, %35, %36, %37, %38, %39, %40, %41, %42, %43, %44, %45, %46, %47, %48, %49, %50, %51, %52, %53, %54, %55, %56, %57, %58, %59, %60, %61, %62, %63}, %64, %65, 1, 1, 1, 0, 1;"
    : "+f"(d[0]), "+f"(d[1]), "+f"(d[2]), "+f"(d[3]), "+f"(d[4]), "+f"(d[5]), "+f"(d[6]), "+f"(d[7]), "+f"(d[8]), "+f"(d[9]), "+f"(d[10]), "+f"(d[11]), "+f"(d[12]), "+f"(d[13]), "+f"(d[14]), "+f"(d[15]), "+f"(d[16]), "+f"(d[17]), "+f"(d[18]), "+f"(d[19]), "+f"(d[20]), "+f"(d[21]), "+f"(d[22]), "+f"(d[23]), "+f"(d[24]), "+f"(d[25]), "+f"(d[26]), "+f"(d[27]), "+f"(d[28]), "+f"(d[29]), "+f"(d[30]), "+f"(d[31]), "+f"(d[32]), "+f"(d[33]), "+f"(d[34]), "+f"(d[35]), "+f"(d[36]), "+f"(d[37]), "+f"(d[38]), "+f"(d[39]), "+f"(d[40]), "+f"(d[41]), "+f"(d[42]), "+f"(d[43]), "+f"(d[44]), "+f"(d[45]), "+f"(d[46]), "+f"(d[47]), "+f"(d[48]), "+f"(d[49]), "+f"(d[50]), "+f"(d[51]), "+f"(d[52]), "+f"(d[53]), "+f"(d[54]), "+f"(d[55]), "+f"(d[56]), "+f"(d[57]), "+f"(d[58]), "+f"(d[59]), "+f"(d[60]), "+f"(d[61]), "+f"(d[62]), "+f"(d[63])
    : "l"(da), "l"(db));
}
__device__ __forceinline__ void wgmma192(float (&d)[128], uint64_t da, uint64_t db) {
  asm volatile("wgmma.mma_async.sync.aligned.m64n192k16.f32.bf16.bf16 "
    "{%0, %1, %2, %3, %4, %5, %6, %7, %8, %9, %10, %11, %12, %13, %14, %15, %16, %17, %18, %19, %20, %21, %22, %23, %24, %25, %26, %27, %28, %29, %30, %31, %32, %33, %34, %35, %36, %37, %38, %39, %40, %41, %42, %43, %44, %45, %46, %47, %48, %49, %50, %51, %52, %53, %54, %55, %56, %57, %58, %59, %60, %61, %62, %63, %64, %65, %66, %67, %68, %69, %70, %71, %72, %73, %74, %75, %76, %77, %78, %79, %80, %81, %82, %83, %84, %85, %86, %87, %88, %89, %90, %91, %92, %93, %94, %95}, %96, %97, 1, 1, 1, 0, 1;"
    : "+f"(d[0]), "+f"(d[1]), "+f"(d[2]), "+f"(d[3]), "+f"(d[4]), "+f"(d[5]), "+f"(d[6]), "+f"(d[7]), "+f"(d[8]), "+f"(d[9]), "+f"(d[10]), "+f"(d[11]), "+f"(d[12]), "+f"(d[13]), "+f"(d[14]), "+f"(d[15]), "+f"(d[16]), "+f"(d[17]), "+f"(d[18]), "+f"(d[19]), "+f"(d[20]), "+f"(d[21]), "+f"(d[22]), "+f"(d[23]), "+f"(d[24]), "+f"(d[25]), "+f"(d[26]), "+f"(d[27]), "+f"(d[28]), "+f"(d[29]), "+f"(d[30]), "+f"(d[31]), "+f"(d[32]), "+f"(d[33]), "+f"(d[34]), "+f"(d[35]), "+f"(d[36]), "+f"(d[37]), "+f"(d[38]), "+f"(d[39]), "+f"(d[40]), "+f"(d[41]), "+f"(d[42]), "+f"(d[43]), "+f"(d[44]), "+f"(d[45]), "+f"(d[46]), "+f"(d[47]), "+f"(d[48]), "+f"(d[49]), "+f"(d[50]), "+f"(d[51]), "+f"(d[52]), "+f"(d[53]), "+f"(d[54]), "+f"(d[55]), "+f"(d[56]), "+f"(d[57]), "+f"(d[58]), "+f"(d[59]), "+f"(d[60]), "+f"(d[61]), "+f"(d[62]), "+f"(d[63]), "+f"(d[64]), "+f"(d[65]), "+f"(d[66]), "+f"(d[67]), "+f"(d[68]), "+f"(d[69]), "+f"(d[70]), "+f"(d[71]), "+f"(d[72]), "+f"(d[73]), "+f"(d[74]), "+f"(d[75]), "+f"(d[76]), "+f"(d[77]), "+f"(d[78]), "+f"(d[79]), "+f"(d[80]), "+f"(d[81]), "+f"(d[82]), "+f"(d[83]), "+f"(d[84]), "+f"(d[85]), "+f"(d[86]), "+f"(d[87]), "+f"(d[88]), "+f"(d[89]), "+f"(d[90]), "+f"(d[91]), "+f"(d[92]), "+f"(d[93]), "+f"(d[94]), "+f"(d[95])
    : "l"(da), "l"(db));
}
__device__ __forceinline__ void wgmma192_init(float (&d)[128], uint64_t da, uint64_t db) {
  asm volatile("wgmma.mma_async.sync.aligned.m64n192k16.f32.bf16.bf16 "
    "{%0, %1, %2, %3, %4, %5, %6, %7, %8, %9, %10, %11, %12, %13, %14, %15, %16, %17, %18, %19, %20, %21, %22, %23, %24, %25, %26, %27, %28, %29, %30, %31, %32, %33, %34, %35, %36, %37, %38, %39, %40, %41, %42, %43, %44, %45, %46, %47, %48, %49, %50, %51, %52, %53, %54, %55, %56, %57, %58, %59, %60, %61, %62, %63, %64, %65, %66, %67, %68, %69, %70, %71, %72, %73, %74, %75, %76, %77, %78, %79, %80, %81, %82, %83, %84, %85, %86, %87, %88, %89, %90, %91, %92, %93, %94, %95}, %96, %97, 0, 1, 1, 0, 1;"
    : "=f"(d[0]), "=f"(d[1]), "=f"(d[2]), "=f"(d[3]), "=f"(d[4]), "=f"(d[5]), "=f"(d[6]), "=f"(d[7]), "=f"(d[8]), "=f"(d[9]), "=f"(d[10]), "=f"(d[11]), "=f"(d[12]), "=f"(d[13]), "=f"(d[14]), "=f"(d[15]), "=f"(d[16]), "=f"(d[17]), "=f"(d[18]), "=f"(d[19]), "=f"(d[20]), "=f"(d[21]), "=f"(d[22]), "=f"(d[23]), "=f"(d[24]), "=f"(d[25]), "=f"(d[26]), "=f"(d[27]), "=f"(d[28]), "=f"(d[29]), "=f"(d[30]), "=f"(d[31]), "=f"(d[32]), "=f"(d[33]), "=f"(d[34]), "=f"(d[35]), "=f"(d[36]), "=f"(d[37]), "=f"(d[38]), "=f"(d[39]), "=f"(d[40]), "=f"(d[41]), "=f"(d[42]), "=f"(d[43]), "=f"(d[44]), "=f"(d[45]), "=f"(d[46]), "=f"(d[47]), "=f"(d[48]), "=f"(d[49]), "=f"(d[50]), "=f"(d[51]), "=f"(d[52]), "=f"(d[53]), "=f"(d[54]), "=f"(d[55]), "=f"(d[56]), "=f"(d[57]), "=f"(d[58]), "=f"(d[59]), "=f"(d[60]), "=f"(d[61]), "=f"(d[62]), "=f"(d[63]), "=f"(d[64]), "=f"(d[65]), "=f"(d[66]), "=f"(d[67]), "=f"(d[68]), "=f"(d[69]), "=f"(d[70]), "=f"(d[71]), "=f"(d[72]), "=f"(d[73]), "=f"(d[74]), "=f"(d[75]), "=f"(d[76]), "=f"(d[77]), "=f"(d[78]), "=f"(d[79]), "=f"(d[80]), "=f"(d[81]), "=f"(d[82]), "=f"(d[83]), "=f"(d[84]), "=f"(d[85]), "=f"(d[86]), "=f"(d[87]), "=f"(d[88]), "=f"(d[89]), "=f"(d[90]), "=f"(d[91]), "=f"(d[92]), "=f"(d[93]), "=f"(d[94]), "=f"(d[95])
    : "l"(da), "l"(db));
}
__device__ __forceinline__ void wgmma192_rs(float (&d)[128], uint32_t a0, uint32_t a1, uint32_t a2, uint32_t a3, uint64_t db) {
  asm volatile("wgmma.mma_async.sync.aligned.m64n192k16.f32.bf16.bf16 "
    "{%0, %1, %2, %3, %4, %5, %6, %7, %8, %9, %10, %11, %12, %13, %14, %15, %16, %17, %18, %19, %20, %21, %22, %23, %24, %25, %26, %27, %28, %29, %30, %31, %32, %33, %34, %35, %36, %37, %38, %39, %40, %41, %42, %43, %44, %45, %46, %47, %48, %49, %50, %51, %52, %53, %54, %55, %56, %57, %58, %59, %60, %61, %62, %63, %64, %65, %66, %67, %68, %69, %70, %71, %72, %73, %74, %75, %76, %77, %78, %79, %80, %81, %82, %83, %84, %85, %86, %87, %88, %89, %90, %91, %92, %93, %94, %95}, {%96, %97, %98, %99}, %100, 1, 1, 1, 1;"
    : "+f"(d[0]), "+f"(d[1]), "+f"(d[2]), "+f"(d[3]), "+f"(d[4]), "+f"(d[5]), "+f"(d[6]), "+f"(d[7]), "+f"(d[8]), "+f"(d[9]), "+f"(d[10]), "+f"(d[11]), "+f"(d[12]), "+f"(d[13]), "+f"(d[14]), "+f"(d[15]), "+f"(d[16]), "+f"(d[17]), "+f"(d[18]), "+f"(d[19]), "+f"(d[20]), "+f"(d[21]), "+f"(d[22]), "+f"(d[23]), "+f"(d[24]), "+f"(d[25]), "+f"(d[26]), "+f"(d[27]), "+f"(d[28]), "+f"(d[29]), "+f"(d[30]), "+f"(d[31]), "+f"(d[32]), "+f"(d[33]), "+f"(d[34]), "+f"(d[35]), "+f"(d[36]), "+f"(d[37]), "+f"(d[38]), "+f"(d[39]), "+f"(d[40]), "+f"(d[41]), "+f"(d[42]), "+f"(d[43]), "+f"(d[44]), "+f"(d[45]), "+f"(d[46]), "+f"(d[47]), "+f"(d[48]), "+f"(d[49]), "+f"(d[50]), "+f"(d[51]), "+f"(d[52]), "+f"(d[53]), "+f"(d[54]), "+f"(d[55]), "+f"(d[56]), "+f"(d[57]), "+f"(d[58]), "+f"(d[59]), "+f"(d[60]), "+f"(d[61]), "+f"(d[62]), "+f"(d[63]), "+f"(d[64]), "+f"(d[65]), "+f"(d[66]), "+f"(d[67]), "+f"(d[68]), "+f"(d[69]), "+f"(d[70]), "+f"(d[71]), "+f"(d[72]), "+f"(d[73]), "+f"(d[74]), "+f"(d[75]), "+f"(d[76]), "+f"(d[77]), "+f"(d[78]), "+f"(d[79]), "+f"(d[80]), "+f"(d[81]), "+f"(d[82]), "+f"(d[83]), "+f"(d[84]), "+f"(d[85]), "+f"(d[86]), "+f"(d[87]), "+f"(d[88]), "+f"(d[89]), "+f"(d[90]), "+f"(d[91]), "+f"(d[92]), "+f"(d[93]), "+f"(d[94]), "+f"(d[95])
    : "r"(a0), "r"(a1), "r"(a2), "r"(a3), "l"(db));
}

__device__ __forceinline__ void wgmma256(float (&d)[128], uint64_t da, uint64_t db) {
  asm volatile("wgmma.mma_async.sync.aligned.m64n256k16.f32.bf16.bf16 "
    "{%0, %1, %2, %3, %4, %5, %6, %7, %8, %9, %10, %11, %12, %13, %14, %15, %16, %17, %18, %19, %20, %21, %22, %23, %24, %25, %26, %27, %28, %29, %30, %31, %32, %33, %34, %35, %36, %37, %38, %39, %40, %41, %42, %43, %44, %45, %46, %47, %48, %49, %50, %51, %52, %53, %54, %55, %56, %57, %58, %59, %60, %61, %62, %63, %64, %65, %66, %67, %68, %69, %70, %71, %72, %73, %74, %75, %76, %77, %78, %79, %80, %81, %82, %83, %84, %85, %86, %87, %88, %89, %90, %91, %92, %93, %94, %95, %96, %97, %98, %99, %100, %101, %102, %103, %104, %105, %106, %107, %108, %109, %110, %111, %112, %113, %114, %115, %116, %117, %118, %119, %120, %121, %122, %123, %124, %125, %126, %127}, %128, %129, 1, 1, 1, 0, 1;"
    : "+f"(d[0]), "+f"(d[1]), "+f"(d[2]), "+f"(d[3]), "+f"(d[4]), "+f"(d[5]), "+f"(d[6]), "+f"(d[7]), "+f"(d[8]), "+f"(d[9]), "+f"(d[10]), "+f"(d[11]), "+f"(d[12]), "+f"(d[13]), "+f"(d[14]), "+f"(d[15]), "+f"(d[16]), "+f"(d[17]), "+f"(d[18]), "+f"(d[19]), "+f"(d[20]), "+f"(d[21]), "+f"(d[22]), "+f"(d[23]), "+f"(d[24]), "+f"(d[25]), "+f"(d[26]), "+f"(d[27]), "+f"(d[28]), "+f"(d[29]), "+f"(d[30]), "+f"(d[31]), "+f"(d[32]), "+f"(d[33]), "+f"(d[34]), "+f"(d[35]), "+f"(d[36]), "+f"(d[37]), "+f"(d[38]), "+f"(d[39]), "+f"(d[40]), "+f"(d[41]), "+f"(d[42]), "+f"(d[43]), "+f"(d[44]), "+f"(d[45]), "+f"(d[46]), "+f"(d[47]), "+f"(d[48]), "+f"(d[49]), "+f"(d[50]), "+f"(d[51]), "+f"(d[52]), "+f"(d[53]), "+f"(d[54]), "+f"(d[55]), "+f"(d[56]), "+f"(d[57]), "+f"(d[58]), "+f"(d[59]), "+f"(d[60]), "+f"(d[61]), "+f"(d[62]), "+f"(d[63]), "+f"(d[64]), "+f"(d[65]), "+f"(d[66]), "+f"(d[67]), "+f"(d[68]), "+f"(d[69]), "+f"(d[70]), "+f"(d[71]), "+f"(d[72]), "+f"(d[73]), "+f"(d[74]), "+f"(d[75]), "+f"(d[76]), "+f"(d[77]), "+f"(d[78]), "+f"(d[79]), "+f"(d[80]), "+f"(d[81]), "+f"(d[82]), "+f"(d[83]), "+f"(d[84]), "+f"(d[85]), "+f"(d[86]), "+f"(d[87]), "+f"(d[88]), "+f"(d[89]), "+f"(d[90]), "+f"(d[91]), "+f"(d[92]), "+f"(d[93]), "+f"(d[94]), "+f"(d[95]), "+f"(d[96]), "+f"(d[97]), "+f"(d[98]), "+f"(d[99]), "+f"(d[100]), "+f"(d[101]), "+f"(d[102]), "+f"(d[103]), "+f"(d[104]), "+f"(d[105]), "+f"(d[106]), "+f"(d[107]), "+f"(d[108]), "+f"(d[109]), "+f"(d[110]), "+f"(d[111]), "+f"(d[112]), "+f"(d[113]), "+f"(d[114]), "+f"(d[115]), "+f"(d[116]), "+f"(d[117]), "+f"(d[118]), "+f"(d[119]), "+f"(d[120]), "+f"(d[121]), "+f"(d[122]), "+f"(d[123]), "+f"(d[124]), "+f"(d[125]), "+f"(d[126]), "+f"(d[127])
    : "l"(da), "l"(db));
}
__device__ __forceinline__ void wgmma256_init(float (&d)[128], uint64_t da, uint64_t db) {
  asm volatile("wgmma.mma_async.sync.aligned.m64n256k16.f32.bf16.bf16 "
    "{%0, %1, %2, %3, %4, %5, %6, %7, %8, %9, %10, %11, %12, %13, %14, %15, %16, %17, %18, %19, %20, %21, %22, %23, %24, %25, %26, %27, %28, %29, %30, %31, %32, %33, %34, %35, %36, %37, %38, %39, %40, %41, %42, %43, %44, %45, %46, %47, %48, %49, %50, %51, %52, %53, %54, %55, %56, %57, %58, %59, %60, %61, %62, %63, %64, %65, %66, %67, %68, %69, %70, %71, %72, %73, %74, %75, %76, %77, %78, %79, %80, %81, %82, %83, %84, %85, %86, %87, %88, %89, %90, %91, %92, %93, %94, %95, %96, %97, %98, %99, %100, %101, %102, %103, %104, %105, %106, %107, %108, %109, %110, %111, %112, %113, %114, %115, %116, %117, %118, %119, %120, %121, %122, %123, %124, %125, %126, %127}, %128, %129, 0, 1, 1, 0, 1;"
    : "=f"(d[0]), "=f"(d[1]), "=f"(d[2]), "=f"(d[3]), "=f"(d[4]), "=f"(d[5]), "=f"(d[6]), "=f"(d[7]), "=f"(d[8]), "=f"(d[9]), "=f"(d[10]), "=f"(d[11]), "=f"(d[12]), "=f"(d[13]), "=f"(d[14]), "=f"(d[15]), "=f"(d[16]), "=f"(d[17]), "=f"(d[18]), "=f"(d[19]), "=f"(d[20]), "=f"(d[21]), "=f"(d[22]), "=f"(d[23]), "=f"(d[24]), "=f"(d[25]), "=f"(d[26]), "=f"(d[27]), "=f"(d[28]), "=f"(d[29]), "=f"(d[30]), "=f"(d[31]), "=f"(d[32]), "=f"(d[33]), "=f"(d[34]), "=f"(d[35]), "=f"(d[36]), "=f"(d[37]), "=f"(d[38]), "=f"(d[39]), "=f"(d[40]), "=f"(d[41]), "=f"(d[42]), "=f"(d[43]), "=f"(d[44]), "=f"(d[45]), "=f"(d[46]), "=f"(d[47]), "=f"(d[48]), "=f"(d[49]), "=f"(d[50]), "=f"(d[51]), "=f"(d[52]), "=f"(d[53]), "=f"(d[54]), "=f"(d[55]), "=f"(d[56]), "=f"(d[57]), "=f"(d[58]), "=f"(d[59]), "=f"(d[60]), "=f"(d[61]), "=f"(d[62]), "=f"(d[63]), "=f"(d[64]), "=f"(d[65]), "=f"(d[66]), "=f"(d[67]), "=f"(d[68]), "=f"(d[69]), "=f"(d[70]), "=f"(d[71]), "=f"(d[72]), "=f"(d[73]), "=f"(d[74]), "=f"(d[75]), "=f"(d[76]), "=f"(d[77]), "=f"(d[78]), "=f"(d[79]), "=f"(d[80]), "=f"(d[81]), "=f"(d[82]), "=f"(d[83]), "=f"(d[84]), "=f"(d[85]), "=f"(d[86]), "=f"(d[87]), "=f"(d[88]), "=f"(d[89]), "=f"(d[90]), "=f"(d[91]), "=f"(d[92]), "=f"(d[93]), "=f"(d[94]), "=f"(d[95]), "=f"(d[96]), "=f"(d[97]), "=f"(d[98]), "=f"(d[99]), "=f"(d[100]), "=f"(d[101]), "=f"(d[102]), "=f"(d[103]), "=f"(d[104]), "=f"(d[105]), "=f"(d[106]), "=f"(d[107]), "=f"(d[108]), "=f"(d[109]), "=f"(d[110]), "=f"(d[111]), "=f"(d[112]), "=f"(d[113]), "=f"(d[114]), "=f"(d[115]), "=f"(d[116]), "=f"(d[117]), "=f"(d[118]), "=f"(d[119]), "=f"(d[120]), "=f"(d[121]), "=f"(d[122]), "=f"(d[123]), "=f"(d[124]), "=f"(d[125]), "=f"(d[126]), "=f"(d[127])
    : "l"(da), "l"(db));
}

namespace {

constexpr int S_LEN = 2048, DM = 1024, DF = 3584;
constexpr int MAXT = 16;
constexpr int MAXPAIRS = 66;
constexpr uint32_t TILE_END = 0xFFFFFFFFu;
constexpr int FLAG_SLEEP = 100;
constexpr int X_STEP = 5;
constexpr int DEF_A = 7, DEF_AW = 5, DEF_G = 8, DEF_R = 4;
constexpr int TAIL = 3;

__device__ __forceinline__ int t_type(uint32_t t) { return t & 3; }
__device__ __forceinline__ int t_mp(uint32_t t) { return (t >> 2) & 7; }
__device__ __forceinline__ int t_idx(uint32_t t) { return (t >> 5) & 31; }
__device__ __forceinline__ int t_k0(uint32_t t) { return (t >> 10) & 63; }
__device__ __forceinline__ int t_nk(uint32_t t) { return (t >> 16) & 63; }
__device__ __forceinline__ int t_sh(uint32_t t) { return (t >> 1) & 1; }
__device__ __forceinline__ int t_deps(uint32_t t, int n) { return ((t_k0(t) + n - 1) >> t_sh(t)) - (t_k0(t) >> t_sh(t)) + 1; }
__device__ __forceinline__ int p1_k(int mp, int k) { return (k + ((mp & 2) << 2)) & 15; }

enum { TM_X1, TM_WQKV, TM_ATTN_ST, TM_ATTN_A, TM_H_A, TM_ACT_A, TM_OUT_ST, TM_OUT16, TM_ACT_ST, TM_WO, TM_WG, TM_WU, TM_WD, TM_COUNT };

struct alignas(64) Params {
  CUtensorMap tm[TM_COUNT];
  const __nv_bfloat16* x;
  const __nv_bfloat16* wo;
  __nv_bfloat16* out;
  int ncta;
  uint32_t sched[MAXPAIRS * MAXT];
};

__device__ __align__(128) __nv_bfloat16 g_attn[S_LEN * DM];
__device__ __align__(128) __nv_bfloat16 g_act[S_LEN * DF];
__device__ __align__(64) uint2 g_xst[S_LEN + 8];
__device__ __align__(128) uint32_t g_csp[16 * 8 * 192];
__device__ __align__(128) uint2 g_rm[DM];
__device__ __align__(128) uint2 g_pdot[16 * S_LEN];
__device__ __align__(128) uint2 g_hmean[S_LEN / 2];
__device__ __align__(128) uint32_t g_hrs[S_LEN];
__device__ __align__(128) uint4 g_halo[16 * 16 * 128];
constexpr int FL_LAUNCH = 0, FL_COPY = 32, FL_OUT = 96, FL_COUNT = FL_OUT + 24 * 32;
__device__ __align__(128) uint32_t g_flags[FL_COUNT];

constexpr int NSTAGE = 4;
constexpr uint32_t STAGE_BYTES = 49152, A_BYTES = 16384;
constexpr uint32_t OFF_STG = NSTAGE * STAGE_BYTES;
constexpr uint32_t OFF_BAR = OFF_STG + 32768;
constexpr uint32_t B_FULL = OFF_BAR, B_EMPTY = OFF_BAR + 32, B_OUTF = OFF_BAR + 64, B_OUTE = OFF_BAR + 96, B_ROW = OFF_BAR + 128,
                   B_HALO = OFF_BAR + 176, B_RM = OFF_BAR + 192, B_EPOCH = OFF_BAR + 200, B_CS = OFF_BAR + 208,
                   B_ROWDONE = OFF_BAR + 216, B_GATE = OFF_BAR + 224, B_COPY = OFF_BAR + 232, B_DUMP = OFF_BAR + 168;
constexpr uint32_t B_HALF = OFF_BAR + 240, B_GO = OFF_BAR + 248, B_DUTY = OFF_BAR + 264;
constexpr uint32_t OFF_MISC = OFF_BAR + 272;
constexpr uint32_t M_EPOCH = OFF_MISC, M_DEP = OFF_MISC + 8, M_PAD = OFF_MISC + 16, M_CS = OFF_MISC + 32, M_RM = M_CS + 768 + 96;
constexpr uint32_t SMEM_BYTES = M_RM + 256;

__device__ __forceinline__ void mbar_init(uint32_t bar, uint32_t cnt) { asm volatile("mbarrier.init.shared::cta.b64 [%0], %1;" :: "r"(bar), "r"(cnt)); }
__device__ __forceinline__ void mbar_arrive(uint32_t bar) { asm volatile("mbarrier.arrive.shared::cta.b64 _, [%0];" :: "r"(bar) : "memory"); }
__device__ __forceinline__ void mbar_arrive_warp(uint32_t bar) {
  __syncwarp();
  asm volatile("{\n.reg .pred p;\nelect.sync _|p, 0xffffffff;\n@p mbarrier.arrive.shared::cta.b64 _, [%0];\n}" :: "r"(bar) : "memory");
}
__device__ __forceinline__ uint32_t mapa(uint32_t addr, uint32_t cta) {
  uint32_t r; asm("mapa.shared::cluster.u32 %0, %1, %2;" : "=r"(r) : "r"(addr), "r"(cta)); return r;
}
__device__ __forceinline__ void mbar_arrive_remote(uint32_t cluster_addr) {
  asm volatile("mbarrier.arrive.shared::cluster.b64 _, [%0];" :: "r"(cluster_addr) : "memory");
}
__device__ __forceinline__ void mbar_wait(uint32_t bar, uint32_t parity) {
  asm volatile("{\n.reg .pred p;\nWAIT_LOOP:\n"
               "mbarrier.try_wait.parity.shared::cta.b64 p, [%0], %1, 5000;\n@!p bra WAIT_LOOP;\n}"
               :: "r"(bar), "r"(parity) : "memory");
}
__device__ __forceinline__ bool mbar_test(uint32_t bar, uint32_t parity) {
  uint32_t ok;
  asm volatile("{\n.reg .pred p;\nmbarrier.test_wait.parity.shared::cta.b64 p, [%1], %2;\nselp.u32 %0, 1, 0, p;\n}"
               : "=r"(ok) : "r"(bar), "r"(parity) : "memory");
  return __all_sync(0xffffffffu, ok != 0);
}
__device__ __forceinline__ void flag_add(uint32_t* flag, uint32_t n) {
  asm volatile("{\n.reg .pred p;\nfence.release.gpu;\nsetp.ne.u64 p, %0, 0;\n@p red.relaxed.gpu.global.add.u32 [%0], %1;\n}" :: "l"(flag), "r"(n) : "memory");
}
__device__ __forceinline__ void fence_async_all() { asm volatile("fence.proxy.async.global;" ::: "memory"); }
__device__ __forceinline__ void fence_async_smem() { asm volatile("fence.proxy.async.shared::cta;" ::: "memory"); }

__device__ __forceinline__ void tma_st3d(const CUtensorMap* m, uint32_t src, int c0, int c1, int c2) {
  asm volatile("{\n.reg .pred p;\nelect.sync _|p, 0xffffffff;\n"
               "@p cp.async.bulk.tensor.3d.global.shared::cta.bulk_group [%0, {%2, %3, %4}], [%1];\n}"
               :: "l"(m), "r"(src), "r"(c0), "r"(c1), "r"(c2) : "memory");
}
__device__ __forceinline__ void tma_add3d(const CUtensorMap* m, uint32_t src, int c0, int c1, int c2) {
  asm volatile("{\n.reg .pred p;\nelect.sync _|p, 0xffffffff;\n"
               "@p cp.reduce.async.bulk.tensor.3d.global.shared::cta.add.tile.bulk_group [%0, {%2, %3, %4}], [%1];\n}"
               :: "l"(m), "r"(src), "r"(c0), "r"(c1), "r"(c2) : "memory");
}
__device__ __forceinline__ void bulk_commit() { asm volatile("cp.async.bulk.commit_group;" ::: "memory"); }
template <int N> __device__ __forceinline__ void bulk_wait_read() { asm volatile("cp.async.bulk.wait_group.read %0;" :: "n"(N) : "memory"); }
__device__ __forceinline__ void bulk_wait_all() { asm volatile("cp.async.bulk.wait_group 0;" ::: "memory"); }

__device__ __forceinline__ void wg_fence() { asm volatile("wgmma.fence.sync.aligned;" ::: "memory"); }
__device__ __forceinline__ void wg_commit() { asm volatile("wgmma.commit_group.sync.aligned;" ::: "memory"); }
template <int N> __device__ __forceinline__ void wg_wait() { asm volatile("wgmma.wait_group.sync.aligned %0;" :: "n"(N) : "memory"); }
__device__ __forceinline__ uint64_t desc64(uint32_t lo) { return ((uint64_t)0x40000040u << 32) | lo; }

__device__ __forceinline__ uint32_t pack2(float lo, float hi) { uint32_t r; asm("cvt.rn.bf16x2.f32 %0, %1, %2;" : "=r"(r) : "f"(hi), "f"(lo)); return r; }
__device__ __forceinline__ float bf_lo(uint32_t v) { return __uint_as_float(v << 16); }
__device__ __forceinline__ float bf_hi(uint32_t v) { return __uint_as_float(v & 0xffff0000u); }
__device__ __forceinline__ uint32_t add2(uint32_t a, uint32_t b) { uint32_t r; asm("add.rn.bf16x2 %0, %1, %2;" : "=r"(r) : "r"(a), "r"(b)); return r; }
__device__ __forceinline__ uint32_t fma2(uint32_t a, uint32_t b, uint32_t c) { uint32_t r; asm("fma.rn.bf16x2 %0, %1, %2, %3;" : "=r"(r) : "r"(a), "r"(b), "r"(c)); return r; }
__device__ __forceinline__ uint32_t mul2(uint32_t a, uint32_t b) { uint32_t r; asm("mul.rn.bf16x2 %0, %1, %2;" : "=r"(r) : "r"(a), "r"(b)); return r; }
__device__ __forceinline__ float tanh_hw(float x) { float y; asm("tanh.approx.f32 %0, %1;" : "=f"(y) : "f"(x)); return y; }
__device__ __forceinline__ float ex2(float x) { float y; asm("ex2.approx.ftz.f32 %0, %1;" : "=f"(y) : "f"(x)); return y; }
__device__ __forceinline__ float rcp(float x) { float y; asm("rcp.approx.ftz.f32 %0, %1;" : "=f"(y) : "f"(x)); return y; }
__device__ __forceinline__ void stsm4(uint32_t addr, uint32_t a, uint32_t b, uint32_t c, uint32_t d) {
  asm volatile("stmatrix.sync.aligned.m8n8.x4.shared.b16 [%0], {%1, %2, %3, %4};" :: "r"(addr), "r"(a), "r"(b), "r"(c), "r"(d) : "memory");
}
__device__ __forceinline__ void stsm4t(uint32_t addr, uint32_t a, uint32_t b, uint32_t c, uint32_t d) {
  asm volatile("stmatrix.sync.aligned.m8n8.x4.trans.shared.b16 [%0], {%1, %2, %3, %4};" :: "r"(addr), "r"(a), "r"(b), "r"(c), "r"(d) : "memory");
}
__device__ __forceinline__ uint4 ld_gpu128(const uint4* p) {
  uint4 v;
  asm volatile("ld.relaxed.gpu.global.v4.u32 {%0, %1, %2, %3}, [%4];" : "=r"(v.x), "=r"(v.y), "=r"(v.z), "=r"(v.w) : "l"(p) : "memory");
  return v;
}
template <int OFF>
__device__ __forceinline__ uint2 ld_gpu64(const void* p) {
  uint2 v;
  asm volatile("ld.relaxed.gpu.global.v2.u32 {%0, %1}, [%2 + %3];" : "=r"(v.x), "=r"(v.y) : "l"(p), "n"(OFF) : "memory");
  return v;
}
__device__ __forceinline__ void st_gpu128_if(bool on, uint4* p, uint32_t a, uint32_t b, uint32_t c, uint32_t d) {
  asm volatile("{\n.reg .pred p;\nsetp.ne.u32 p, %5, 0;\n@p st.relaxed.gpu.global.v4.u32 [%0], {%1, %2, %3, %4};\n}"
               :: "l"(p), "r"(a), "r"(b), "r"(c), "r"(d), "r"((uint32_t)on) : "memory");
}
__device__ __forceinline__ void st_gpu64_if(bool on, uint2* p, uint32_t a, uint32_t b) {
  asm volatile("{\n.reg .pred p;\nsetp.ne.u32 p, %3, 0;\n@p st.relaxed.gpu.global.v2.u32 [%0], {%1, %2};\n}"
               :: "l"(p), "r"(a), "r"(b), "r"((uint32_t)on) : "memory");
}
template <int OFF>
__device__ __forceinline__ uint32_t ld_gpu32(const void* p) {
  uint32_t v;
  asm volatile("ld.relaxed.gpu.global.u32 %0, [%1 + %2];" : "=r"(v) : "l"(p), "n"(OFF) : "memory");
  return v;
}
__device__ __forceinline__ void st_gpu32_if(bool on, uint32_t* p, uint32_t a) {
  asm volatile("{\n.reg .pred p;\nsetp.ne.u32 p, %2, 0;\n@p st.relaxed.gpu.global.u32 [%0], %1;\n}" :: "l"(p), "r"(a), "r"((uint32_t)on) : "memory");
}
__device__ __forceinline__ uint32_t tagged(float v, uint32_t tag) { return __byte_perm(__float_as_uint(v), tag, 0x3214); }
__device__ __forceinline__ float untagged(uint32_t v) { return __uint_as_float(v & ~255u); }
__device__ __forceinline__ uint32_t lds32(uint32_t a) {
  uint32_t v;
  asm volatile("ld.shared.u32 %0, [%1];" : "=r"(v) : "r"(a) : "memory");
  return v;
}
__device__ __forceinline__ uint4 lds128(uint32_t a) {
  uint4 v;
  asm volatile("ld.shared.v4.u32 {%0, %1, %2, %3}, [%4];" : "=r"(v.x), "=r"(v.y), "=r"(v.z), "=r"(v.w) : "r"(a) : "memory");
  return v;
}
__device__ __forceinline__ void ldsm4(uint32_t addr, uint32_t& a, uint32_t& b, uint32_t& c, uint32_t& d) {
  asm volatile("ldmatrix.sync.aligned.m8n8.x4.shared.b16 {%0, %1, %2, %3}, [%4];" : "=r"(a), "=r"(b), "=r"(c), "=r"(d) : "r"(addr) : "memory");
}
__device__ __forceinline__ uint32_t movmat(uint32_t a) { uint32_t d; asm volatile("movmatrix.sync.aligned.m8n8.trans.b16 %0, %1;" : "=r"(d) : "r"(a)); return d; }
__device__ __forceinline__ void mma16(float (&d)[4], uint32_t a0, uint32_t a1, uint32_t a2, uint32_t a3, uint32_t b0, uint32_t b1) {
  asm volatile("mma.sync.aligned.m16n8k16.row.col.f32.bf16.bf16.f32 {%0, %1, %2, %3}, {%4, %5, %6, %7}, {%8, %9}, {%0, %1, %2, %3};"
               : "+f"(d[0]), "+f"(d[1]), "+f"(d[2]), "+f"(d[3]) : "r"(a0), "r"(a1), "r"(a2), "r"(a3), "r"(b0), "r"(b1));
}
__device__ __forceinline__ void mma16_init(float (&d)[4], uint32_t a0, uint32_t a1, uint32_t a2, uint32_t a3, uint32_t b0, uint32_t b1) {
  asm volatile("mma.sync.aligned.m16n8k16.row.col.f32.bf16.bf16.f32 {%0, %1, %2, %3}, {%4, %5, %6, %7}, {%8, %9}, {%10, %10, %10, %10};"
               : "=f"(d[0]), "=f"(d[1]), "=f"(d[2]), "=f"(d[3]) : "r"(a0), "r"(a1), "r"(a2), "r"(a3), "r"(b0), "r"(b1), "f"(0.f));
}
__device__ __forceinline__ float quad_sum(float v) { v += __shfl_xor_sync(0xffffffffu, v, 1); return v + __shfl_xor_sync(0xffffffffu, v, 2); }
__device__ __forceinline__ float quad_max(float v) { v = fmaxf(v, __shfl_xor_sync(0xffffffffu, v, 1)); return fmaxf(v, __shfl_xor_sync(0xffffffffu, v, 2)); }

__device__ __forceinline__ int fresh_tid() { int t; asm volatile("mov.u32 %0, %%tid.x;" : "=r"(t)); return t; }

__device__ __forceinline__ void mbar_spin(uint32_t bar, uint32_t parity) {
  asm volatile("{\n.reg .pred p;\nWAIT_LOOP:\nmbarrier.try_wait.parity.shared::cta.b64 p, [%0], %1;\n@!p bra WAIT_LOOP;\n}" :: "r"(bar), "r"(parity) : "memory");
}

struct Cons {
  uint32_t sb;
  uint32_t empty_r;
  uint32_t srow;
  int w, rank;
  uint32_t s, ph;
  uint32_t prev;
  uint32_t phb;
};

__device__ __forceinline__ void release_prev(Cons& c) {
  if (c.prev < NSTAGE && c.empty_r) mbar_arrive_remote(c.empty_r + 8 * c.prev);
}

template <int N, bool FIRST = false, bool WAIT = true>
__device__ __forceinline__ void mma_step(Cons& c, float (&acc)[128]) {
  if (WAIT) mbar_spin(c.sb + B_FULL + 8 * c.s, c.ph);
  const uint32_t st = ((c.sb & 0x3FFFF) >> 4) + c.s * (STAGE_BYTES >> 4);
  const uint32_t da = st + c.w * 512 + (1u << 16);
  const uint32_t db = st + (A_BYTES >> 4) + ((N == 192 ? 256u : 512u) << 16);
  wg_fence();
#pragma unroll
  for (int kk = 0; kk < 4; kk++) {
    const uint32_t bo = N == 192 ? (kk >> 1) * 768 + (kk & 1) * 128 : kk * 128;
    if (FIRST && kk == 0) {
      if (N == 192) wgmma192_init(acc, desc64(da), desc64(db));
      else wgmma256_init(acc, desc64(da), desc64(db));
    } else {
      if (N == 192) wgmma192(acc, desc64(da + kk * 2), desc64(db + bo));
      else wgmma256(acc, desc64(da + kk * 2), desc64(db + bo));
    }
    if (kk == 0) {
      wg_commit();
      wg_wait<1>();
      release_prev(c);
    }
  }
  wg_commit();
  c.prev = c.s;
  if (++c.s == NSTAGE) { c.s = 0; c.ph ^= 1; }
}

template <int CHUNK>
__device__ __forceinline__ uint32_t srow(const Cons& c) {
  if (CHUNK == 0) return c.srow;
  uint32_t r;
  asm volatile("xor.b32 %0, %1, %2;" : "=r"(r) : "r"(c.srow), "n"(CHUNK << 4));
  return r;
}
__device__ __forceinline__ void out_acquire(Cons& c, int sub) {
  mbar_spin(c.sb + B_OUTE + c.w * 16 + sub * 8, ((c.phb >> sub) & 1) ^ 1);
  c.phb ^= 1u << sub;
}
__device__ __forceinline__ void out_publish(const Cons& c, int sub) {
  fence_async_smem();
  mbar_arrive_warp(c.sb + B_OUTF + c.w * 16 + sub * 8);
}

__device__ __forceinline__ float asf(uint32_t v) { return __uint_as_float(v); }
__device__ __forceinline__ uint32_t asu(float v) { return __float_as_uint(v); }

__device__ __forceinline__ void sched_fence(uint32_t sb) {
  asm volatile("{\n.reg .pred p;\n.reg .u32 t;\nmov.u32 t, %%clock;\nsetp.eq.u32 p, t, 0;\n@p st.shared.u32 [%0], t;\n}" :: "r"(sb + M_PAD) : "memory");
}

template <int N, bool FIRST = false, bool WAIT = true>
__device__ __forceinline__ void next_step(Cons& c, float (&acc)[128]) {
  if (N) {
    if (!WAIT) {
      sched_fence(c.sb);
      asm volatile("bar.sync 3, 256;" ::: "memory");
    }
    mma_step<N, FIRST, WAIT>(c, acc);
    sched_fence(c.sb);
  }
}

__device__ __forceinline__ void p1_park(const Cons& c, const float (&acc)[128], uint32_t (&lo)[24], uint32_t (&hi)[24], int g, uint32_t tile) {
#pragma unroll
  for (int j = 8; j < 24; j++) hi[j] = pack2(acc[4 * j + 2], acc[4 * j + 3]);
  const int l = fresh_tid() & 31;
  if (g < 8) {
#pragma unroll
    for (int i = 0; i < 4; i++)
      stsm4(c.sb + OFF_STG + (g >> 2) * 16384 + (g & 3) * 2048 + l * 16 + i * 512, hi[8 + 4 * i], hi[9 + 4 * i], hi[10 + 4 * i], hi[11 + 4 * i]);
    mbar_arrive_warp(c.sb + B_HALO + (g >> 2) * 8);
  } else {
    uint4* box = g_halo + ((t_mp(tile) * 2 + c.rank) * 16 + t_idx(tile)) * 128 + l;
#pragma unroll
    for (int i = 0; i < 4; i++) st_gpu128_if(t_mp(tile) < 7, box + i * 32, ~hi[8 + 4 * i], ~hi[9 + 4 * i], ~hi[10 + 4 * i], ~hi[11 + 4 * i]);
  }
#pragma unroll
  for (int j = 0; j < 8; j++) hi[j] = pack2(acc[4 * j + 2], acc[4 * j + 3]);
#pragma unroll
  for (int j = 0; j < 24; j++) lo[j] = pack2(acc[4 * j], acc[4 * j + 1]);
}

__device__ __forceinline__ void p1_centre(const Cons& c, float (&acc)[128], float mu0, float mu1) {
  const uint32_t on = (fresh_tid() & 3) == 0 ? 0xffffffffu : 0u;
  const uint32_t h0 = pack2(-mu0, -mu0), h1 = pack2(-mu1, -mu1);
  const float r0 = -mu0 - bf_lo(h0), r1 = -mu1 - bf_lo(h1);
  const uint32_t a0 = h0 & on, a1 = h1 & on, a2 = pack2(r0, r0) & on, a3 = pack2(r1, r1) & on;
  wg_fence();
  wgmma192_rs(acc, a0, a1, a2, a3, ((uint64_t)2 << 32) | (((c.sb + M_CS) & 0x3FFFF) >> 4));
  wg_commit();
}

template <int DEFER>
__device__ __forceinline__ void p1_attention(Cons& c, float (&acc)[128], uint32_t (&lo)[24], uint32_t (&hi)[24], const float (&ev)[8], uint32_t tile) {
  next_step<DEFER, true>(c, acc);
  if (DEFER < 256) next_step<DEFER>(c, acc);
  const int tw = fresh_tid() & 127, l = tw & 31, q = l & 3, r = l >> 2;
  const uint32_t mine = c.sb + OFF_STG + c.w * 16384 + (tw >> 5) * 2048 + l * 16;
#pragma unroll
  for (int j = 16; j < 24; j++) { lo[j] = movmat(lo[j]); hi[j] = movmat(hi[j]); }
  const bool c0 = 2 * q <= r, c1 = 2 * q + 1 <= r;
  constexpr float QS = 0.17677669529663687f * 1.4426950408889634f;
  const float kl0 = c0 ? ev[4] : ev[2], kl1 = c1 ? ev[5] : ev[3], ql0 = ev[0] * QS * kl0, ql1 = ev[0] * QS * kl1;
  const float kh0 = c0 ? ev[6] : ev[4], kh1 = c1 ? ev[7] : ev[5], qh0 = ev[1] * QS * kh0, qh1 = ev[1] * QS * kh1;
  next_step<DEFER>(c, acc);
  mbar_spin(c.sb + B_HALO + c.w * 8, (c.phb >> 2) & 1);
  c.phb ^= 4;
  float sp[2][4], s0[2][4], s1[2][4];
  {
    uint32_t kp[8];
    ldsm4(mine, kp[0], kp[1], kp[2], kp[3]);
    ldsm4(mine + 512, kp[4], kp[5], kp[6], kp[7]);
    if (DEFER) { mbar_spin(c.sb + B_FULL + 8 * c.s, c.ph); sched_fence(c.sb); }
#pragma unroll
    for (int h = 0; h < 2; h++) {
      const int a = 4 * h, b = a + 2;
      mma16_init(s0[h], lo[a], hi[a], lo[a + 1], hi[a + 1], lo[8 + a], lo[9 + a]);
      mma16_init(s1[h], lo[a], hi[a], lo[a + 1], hi[a + 1], hi[8 + a], hi[9 + a]);
      mma16_init(sp[h], lo[a], hi[a], lo[a + 1], hi[a + 1], kp[a], kp[a + 1]);
      mma16(s0[h], lo[b], hi[b], lo[b + 1], hi[b + 1], lo[8 + b], lo[9 + b]);
      mma16(s1[h], lo[b], hi[b], lo[b + 1], hi[b + 1], hi[8 + b], hi[9 + b]);
      mma16(sp[h], lo[b], hi[b], lo[b + 1], hi[b + 1], kp[b], kp[b + 1]);
    }
  }
  next_step<DEFER, false, false>(c, acc);
  float x[4][2];
  {
    const bool first = (t_mp(tile) | c.w | (tw >> 5)) == 0;
#pragma unroll
    for (int h = 0; h < 2; h++) {
      x[h][0] = first && !c0 ? -INFINITY : (c0 ? s0[h][0] : sp[h][0]) * ql0;
      x[h][1] = first && !c1 ? -INFINITY : (c1 ? s0[h][1] : sp[h][1]) * ql1;
      x[2 + h][0] = (c0 ? s1[h][2] : s0[h][2]) * qh0;
      x[2 + h][1] = (c1 ? s1[h][3] : s0[h][3]) * qh1;
    }
#pragma unroll
    for (int i = 0; i < 4; i++) {
      const float m = quad_max(fmaxf(x[i][0], x[i][1]));
      x[i][0] = ex2(x[i][0] - m); x[i][1] = ex2(x[i][1] - m);
    }
  }
  if (DEFER < 256) next_step<DEFER>(c, acc);
  float ol[4][4], oh[4][4];
  {
    uint32_t vp[4][4], pb[4][2];
#pragma unroll
    for (int m = 0; m < 4; m++) {
      asm volatile("ldmatrix.sync.aligned.m8n8.x2.trans.shared.b16 {%0, %1}, [%2];" : "=r"(vp[m][0]), "=r"(vp[m][1]) : "r"(mine + 1024 + m * 256) : "memory");
      asm volatile("mov.b32 %0, %2;\nmov.b32 %1, %3;" : "=r"(vp[m][2]), "=r"(vp[m][3]) : "r"(lo[16 + 2 * m]), "r"(lo[17 + 2 * m]));
    }
    const uint32_t cur = (c0 ? 0x0000ffffu : 0u) | (c1 ? 0xffff0000u : 0u);
#pragma unroll
    for (int i = 0; i < 4; i++) {
      const float inv = rcp(quad_sum(x[i][0] + x[i][1]));
      const uint32_t pr = pack2(x[i][0] * inv * (i < 2 ? kl0 : kh0), x[i][1] * inv * (i < 2 ? kl1 : kh1));
      pb[i][0] = pr & ~cur; pb[i][1] = pr & cur;
    }
    if (DEFER) { mbar_spin(c.sb + B_FULL + 8 * c.s, c.ph); sched_fence(c.sb); }
#pragma unroll
    for (int m = 0; m < 4; m++) {
      mma16_init(oh[m], lo[16 + 2 * m], lo[17 + 2 * m], hi[16 + 2 * m], hi[17 + 2 * m], pb[2 + (m >> 1)][0], pb[2 + (m >> 1)][1]);
      mma16_init(ol[m], vp[m][0], vp[m][1], vp[m][2], vp[m][3], pb[m >> 1][0], pb[m >> 1][1]);
    }
  }
  next_step<DEFER, false, false>(c, acc);
#pragma unroll
  for (int m = 0; m < 4; m++)
    stsm4t(c.srow ^ (m << 5), pack2(ol[m][0], ol[m][1]), pack2(oh[m][0], oh[m][1]), pack2(ol[m][2], ol[m][3]), pack2(oh[m][2], oh[m][3]));
  next_step<DEFER>(c, acc);
  out_publish(c, 0);
  mbar_spin(c.sb + B_RM, 0);
  float d[4] = {0.f, 0.f, 0.f, 0.f};
#pragma unroll
  for (int m = 0; m < 4; m += 2) {
    const uint4 rm = lds128(c.sb + M_RM + m * 64 + r * 16);
    d[0] = fmaf(ol[m][0], asf(rm.x), fmaf(ol[m][2], asf(rm.y), fmaf(ol[m + 1][0], asf(rm.z), fmaf(ol[m + 1][2], asf(rm.w), d[0]))));
    d[1] = fmaf(ol[m][1], asf(rm.x), fmaf(ol[m][3], asf(rm.y), fmaf(ol[m + 1][1], asf(rm.z), fmaf(ol[m + 1][3], asf(rm.w), d[1]))));
    d[2] = fmaf(oh[m][0], asf(rm.x), fmaf(oh[m][2], asf(rm.y), fmaf(oh[m + 1][0], asf(rm.z), fmaf(oh[m + 1][2], asf(rm.w), d[2]))));
    d[3] = fmaf(oh[m][1], asf(rm.x), fmaf(oh[m][3], asf(rm.y), fmaf(oh[m + 1][1], asf(rm.z), fmaf(oh[m + 1][3], asf(rm.w), d[3]))));
  }
  const bool up = l & 16, odd = l & 8;
  const float e0 = (up ? d[2] : d[0]) + __shfl_xor_sync(0xffffffffu, up ? d[0] : d[2], 16);
  const float e1 = (up ? d[3] : d[1]) + __shfl_xor_sync(0xffffffffu, up ? d[1] : d[3], 16);
  float f = (odd ? e1 : e0) + __shfl_xor_sync(0xffffffffu, odd ? e0 : e1, 8);
  f += __shfl_xor_sync(0xffffffffu, f, 4);
  st_gpu64_if(!(l & 4),
              g_pdot + t_idx(tile) * S_LEN + c.rank * 1024 + t_mp(tile) * 128 + c.w * 64 + (tw >> 5) * 16 + (l >> 4) * 8 + 2 * q + ((l >> 3) & 1),
              asu(f), lds32(c.sb + M_EPOCH));
}

__device__ __forceinline__ void cs_accumulate(const Cons& c, uint32_t (&pk)[64], uint32_t off) {
#pragma unroll
  for (int g = 0; g < 3; g++) {
    uint32_t a, b;
    asm volatile("ld.shared.v2.b32 {%0, %1}, [%2];" : "=r"(a), "=r"(b) : "r"(off + c.prev * STAGE_BYTES + g * 4096) : "memory");
    pk[4 * g] = asu(asf(pk[4 * g]) + bf_lo(a)); pk[4 * g + 1] = asu(asf(pk[4 * g + 1]) + bf_hi(a));
    pk[4 * g + 2] = asu(asf(pk[4 * g + 2]) + bf_lo(b)); pk[4 * g + 3] = asu(asf(pk[4 * g + 3]) + bf_hi(b));
  }
}
__device__ __forceinline__ void cs_dump(const Cons& c, const uint32_t (&pk)[64]) {
  const int t = fresh_tid();
  const bool up = t & 16;
#pragma unroll
  for (int g = 0; g < 3; g++) {
    const float a = asf(up ? pk[4 * g + 2] : pk[4 * g]) + __shfl_xor_sync(0xffffffffu, asf(up ? pk[4 * g] : pk[4 * g + 2]), 16);
    const float b = asf(up ? pk[4 * g + 3] : pk[4 * g + 1]) + __shfl_xor_sync(0xffffffffu, asf(up ? pk[4 * g + 1] : pk[4 * g + 3]), 16);
    asm volatile("st.shared.v2.f32 [%0], {%1, %2};"
                 :: "r"(c.sb + OFF_STG + 16384 + (t >> 5) * 768 + g * 256 + (t & 15) * 16 + (t & 16) / 2), "f"(a), "f"(b) : "memory");
  }
  mbar_arrive_warp(c.sb + B_DUMP);
  mbar_spin(c.sb + B_EPOCH, 0);
}
__device__ __forceinline__ void cs_publish(const Cons& c, uint32_t tile) {
  const int t = min(fresh_tid(), 191);
  mbar_spin(c.sb + B_DUMP, 0);
  float v[8];
#pragma unroll
  for (int g = 0; g < 8; g++) v[g] = asf(lds32(c.sb + OFF_STG + 16384 + g * 768 + t * 4));
  st_gpu32_if(t_mp(tile) < 4, g_csp + (t_idx(tile) * 8 + (t_mp(tile) & 3) * 2 + c.rank) * 192 + t,
              tagged(((v[0] + v[1]) + (v[2] + v[3])) + ((v[4] + v[5]) + (v[6] + v[7])), lds32(c.sb + M_EPOCH)));
}

__device__ __forceinline__ void cs_fetch(uint32_t (&cs)[8], uint32_t tile) {
  const uint32_t* part = g_csp + t_idx(tile) * (8 * 192) + min(fresh_tid(), 191);
#pragma unroll
  for (int i = 0; i < 8; i++) cs[i] = ld_gpu32<0>(part + i * 192);
}
__device__ __forceinline__ void cs_finish(const Cons& c, uint32_t (&cs)[8], uint32_t tile, uint32_t tag) {
  while (true) {
    uint32_t bad = 0;
#pragma unroll
    for (int i = 0; i < 8; i++) bad |= cs[i] ^ tag;
    if (!__any_sync(0xffffffffu, (bad & 255) != 0)) break;
    cs_fetch(cs, tile);
  }
  const float sum = ((untagged(cs[0]) + untagged(cs[1])) + (untagged(cs[2]) + untagged(cs[3]))) + ((untagged(cs[4]) + untagged(cs[5])) + (untagged(cs[6]) + untagged(cs[7])));
  const uint32_t h = pack2(sum, sum), col = min(fresh_tid(), 191);
  asm volatile("st.shared.u16 [%0], %1;\nst.shared.u16 [%0 + 16], %2;"
               :: "r"(c.sb + M_CS + (col >> 3) * 32 + (col & 7) * 2), "h"((uint16_t)h), "h"((uint16_t)pack2(sum - bf_lo(h), 0.f)) : "memory");
  fence_async_smem();
}

template <int C>
__device__ __forceinline__ void g_chunk(Cons& c, uint32_t (&pk)[64], float (&ev)[8]) {
  constexpr float C0 = 0.7978845608028654f, C1 = 0.044715f * 0.7978845608028654f;
  if ((C & 3) == 0) out_acquire(c, C >> 2);
  uint32_t o[4];
#pragma unroll
  for (int i = 0; i < 4; i++) {
    const float rs = ev[i & 1];
    const float k0 = C0 * rs, k1 = C1 * rs * rs * rs, k2 = 0.5f * rs * rs;
    const float g0 = bf_lo(pk[4 * C + i]), g1 = bf_hi(pk[4 * C + i]);
    const float t0 = tanh_hw(g0 * fmaf(g0 * g0, k1, k0)), t1 = tanh_hw(g1 * fmaf(g1 * g1, k1, k0));
    o[i] = mul2(pack2(g0 * fmaf(t0, k2, k2), g1 * fmaf(t1, k2, k2)), pk[32 + 4 * C + i]);
  }
  stsm4(srow<(C & 3) * 2>(c) + (C >> 2) * 8192, o[0], o[1], o[2], o[3]);
  if ((C & 3) == 3) out_publish(c, C >> 2);
}

template <int C>
__device__ __forceinline__ void r_chunk(Cons& c, const uint32_t (&pk)[64], const float (&ev)[8]) {
  uint32_t o[16];
#pragma unroll
  for (int i = 0; i < 16; i++) o[i] = add2(pk[16 * C + i], asu(ev[i & 1]));
  out_acquire(c, C & 1);
  stsm4(srow<0>(c) + (C & 1) * 8192, o[0], o[1], o[2], o[3]);
  stsm4(srow<2>(c) + (C & 1) * 8192, o[4], o[5], o[6], o[7]);
  stsm4(srow<4>(c) + (C & 1) * 8192, o[8], o[9], o[10], o[11]);
  stsm4(srow<6>(c) + (C & 1) * 8192, o[12], o[13], o[14], o[15]);
  out_publish(c, C & 1);
}
template <int H>
__device__ __forceinline__ void mma_half(const Cons& c, float (&acc)[64], int i0, int i1) {
#pragma unroll 1
  for (int i = i0; i < i1; i++) {
    const uint32_t s = (c.s + i) & 3;
    if (H == 0) mbar_spin(c.sb + B_FULL + 8 * s, c.ph ^ ((c.s + i) >> 2));
    wg_fence();
    const uint32_t st = ((c.sb & 0x3FFFF) >> 4) + s * (STAGE_BYTES >> 4);
    const uint32_t da = st + c.w * 512 + (1u << 16), db = st + (A_BYTES >> 4) + H * 1024 + (512u << 16);
#pragma unroll
    for (int kk = 0; kk < 4; kk++) wgmma128(acc, desc64(da + kk * 2), desc64(db + kk * 128));
    wg_commit();
  }
}
__device__ __forceinline__ void release_tail(Cons& c, bool hold) {
#pragma unroll 1
  for (int i = 0; i < TAIL; i++) {
    c.prev = hold ? NSTAGE : c.s;
    release_prev(c);
    if (++c.s == NSTAGE) { c.s = 0; c.ph ^= 1; }
  }
  c.prev = NSTAGE;
}
template <int C, bool ADD>
__device__ __forceinline__ void half_out(const Params& p, const Cons& c, const float (&acc)[64], const float (&ev)[8], bool own,
                                         uint32_t mine, int col, int row) {
#pragma unroll
  for (int i = 4 * C; i < 4 * C + 4; i++) {
    uint32_t o[4];
#pragma unroll
    for (int j = 0; j < 4; j++) {
      o[j] = pack2(acc[8 * i + 2 * j], acc[8 * i + 2 * j + 1]);
      if (ADD) o[j] = add2(o[j], asu(ev[j & 1]));
    }
    stsm4((c.srow ^ ((i & 3) << 5)) + C * 8192, o[0], o[1], o[2], o[3]);
  }
  fence_async_smem();
  __syncwarp();
  if (own) tma_add3d(&p.tm[TM_OUT16], mine + C * 8192, col + C * 64, row, 0);
  else mbar_arrive_warp(c.sb + B_OUTF + c.w * 16 + C * 8);
  sched_fence(c.sb);
}

template <int N>
__device__ __forceinline__ void mma_run(Cons& c, float (&acc)[128], int k0, int k1) {
#pragma unroll 1
  for (int k = k0; k < k1; k++) mma_step<N>(c, acc);
}

__device__ __forceinline__ void tile_end(Cons& c) {
  wg_wait<0>();
  release_prev(c);
  c.prev = NSTAGE;
}

__device__ __forceinline__ void stagger_wait(Cons& c) {
  if (c.w == 1) {
    wg_wait<0>();
    release_prev(c);
    c.prev = NSTAGE;
    asm volatile("bar.sync 7, 256;" ::: "memory");
  }
}

struct RowMeans {
  const uint4* src;
  uint4 v[4], x;
};
__device__ __forceinline__ int first_row(const Cons& c, uint32_t tile) {
  const int t = fresh_tid();
  return (t_mp(tile) * 2 + c.rank) * 128 + (t >> 5) * 16 + ((t & 31) >> 2);
}
__device__ __forceinline__ int mean_slot(const Cons& c, uint32_t tile) {
  const int t = fresh_tid();
  return (t & 4) * 128 + (t_mp(tile) * 2 + c.rank) * 32 + (t >> 5) * 4 + (t & 3);
}
__device__ __forceinline__ void row_means_fetch(RowMeans& s) {
#pragma unroll
  for (int i = 0; i < 4; i++) s.v[i] = ld_gpu128(s.src + i * (2 * S_LEN));
}
__device__ __forceinline__ void row_means_load(RowMeans& s, const Cons& c, uint32_t tile) {
  s.src = nullptr;
  s.v[0] = s.v[1] = s.v[2] = s.v[3] = s.x = make_uint4(0, 0, 0, 0);
  if ((tile >> 22) & 1) {
    const int o = mean_slot(c, tile);
    if (t_type(tile) == 1) {
      s.x = ld_gpu128((const uint4*)(g_xst + 8) + o);
      s.src = (const uint4*)g_pdot + ((fresh_tid() >> 3) & 3) * (S_LEN / 2) + o;
      row_means_fetch(s);
    } else {
      asm volatile("ld.relaxed.gpu.global.u32 %0, [%1];" : "=r"(s.x.x) : "l"(g_hmean + o) : "memory");
    }
  }
}
__device__ __forceinline__ void row_means_finish(RowMeans& s, const Cons& c, uint32_t tile, float (&ev)[8]) {
  ev[0] = ev[1] = 0.f;
  if ((tile >> 22) & 1) {
    uint32_t m = s.x.x;
    if (t_type(tile) == 1) {
      const uint32_t tag = lds32(c.sb + M_EPOCH);
      while (true) {
        uint32_t bad = 0;
#pragma unroll
        for (int i = 0; i < 4; i++) bad |= (s.v[i].y ^ tag) | (s.v[i].w ^ tag);
        if (!__any_sync(0xffffffffu, bad != 0)) break;
        row_means_fetch(s);
      }
      float a = (asf(s.v[0].x) + asf(s.v[1].x)) + (asf(s.v[2].x) + asf(s.v[3].x));
      float b = (asf(s.v[0].z) + asf(s.v[1].z)) + (asf(s.v[2].z) + asf(s.v[3].z));
      a += __shfl_xor_sync(0xffffffffu, a, 8); b += __shfl_xor_sync(0xffffffffu, b, 8);
      a += __shfl_xor_sync(0xffffffffu, a, 16); b += __shfl_xor_sync(0xffffffffu, b, 16);
      m = pack2(a + asf(s.x.x), b + asf(s.x.z));
      st_gpu64_if(t_idx(tile) == 0 && (fresh_tid() & 24) == 0, g_hmean + mean_slot(c, tile), m, tag);
      m ^= 0x80008000u;
    }
    const int r = (fresh_tid() & 31) >> 2, from = (r & 1) * 4 + (r >> 2), sel = r & 2 ? 0x3232 : 0x1010;
    ev[0] = asf(__byte_perm(__shfl_sync(0xffffffffu, m, from), 0, sel));
    ev[1] = asf(__byte_perm(__shfl_sync(0xffffffffu, m, from + 2), 0, sel));
  }
}

__device__ __forceinline__ void consumer(const Params& p, uint32_t sb, int w, int rank, int pair) {
  Cons c;
  c.sb = sb; c.w = w; c.rank = rank;
  const int t0 = threadIdx.x & 127;
  c.empty_r = __shfl_sync(0xffffffffu, t0 < 2 ? mapa(sb + B_EMPTY, t0 & 1) : 0u, t0 & 31);
  c.srow = __shfl_sync(0xffffffffu, sb + OFF_STG + w * 16384 + ((t0 >> 5) * 16 + (t0 & 15)) * 128 + ((((t0 >> 4) & 1) ^ (t0 & 7)) << 4), t0 & 31);
  c.s = 0; c.ph = 0; c.prev = NSTAGE; c.phb = 0;
  float acc[128];
  uint32_t pk[64];
  float ev[8];
  const uint32_t* sched = p.sched + pair * MAXT;
  int ti = 0;
  uint32_t tile = __shfl_sync(0xffffffffu, sched[0], 0);
  const int g = __shfl_sync(0xffffffffu, (threadIdx.x >> 5) + 1, 0);
  int k;
  uint32_t cs[8];

  mma_step<192, true>(c, acc);
  {
    const int t = fresh_tid(), row = (t_mp(tile) & 1) * 16 + (t >> 4);
    const uint32_t off = sb + A_BYTES + rank * 12288 + row * 128 + ((((t >> 1) ^ row) & 7) << 4) + (t & 1) * 8;
#pragma unroll
    for (int i = 0; i < 12; i++) pk[i] = 0;
#pragma unroll 1
    for (k = 1; k < 12; k++) {
      if ((unsigned)(k - X_STEP) < 2u) mbar_arrive_warp(sb + B_GO + 8 * (k - X_STEP));
      if (k < 9) cs_accumulate(c, pk, off);
      if (k == 9) cs_dump(c, pk);
      if (k == 10) cs_publish(c, tile);
      mma_step<192>(c, acc);
    }
    cs_fetch(cs, tile);
  }
started192:
  {
    const uint32_t next = __shfl_sync(0xffffffffu, sched[ti + 1], 0);
    mma_run<192>(c, acc, k, 13);
    const int t = fresh_tid(), q = t & 3, r = (t & 31) >> 2;
    const uint32_t tag = lds32(sb + M_EPOCH);
    const int base = rank * 1024 + t_mp(tile) * 128 + (t >> 5) * 16;
    const uint2* own = g_xst + base + r;
    const uint4* before = (const uint4*)(g_xst + base) + q + (base & 1023 ? 0 : 4);
    uint2 e0 = ld_gpu64<64>(own), e1 = ld_gpu64<128>(own);
    uint4 kp = ld_gpu128(before);
    mbar_spin(sb + B_OUTE + (g >> 2 ? 16 : 0), (c.phb & 1) ^ 1);
    c.phb ^= 1;
#pragma unroll 1
    for (int i = t_nk(tile) - 13; i > 0; i--) {
      if (i == 2) {
        if (ti == 0) cs_finish(c, cs, tile, tag);
        mbar_arrive_warp(sb + B_CS);
      }
      if (i == 1) stagger_wait(c);
      mma_step<192>(c, acc);
    }
    while (true) {
      if (!__any_sync(0xffffffffu, (((e0.y ^ tag) | (e1.y ^ tag) | (kp.y ^ tag) | (kp.w ^ tag)) & 255) != 0)) break;
      e0 = ld_gpu64<64>(own); e1 = ld_gpu64<128>(own);
      kp = ld_gpu128(before);
    }
    mbar_spin(sb + B_CS, (c.phb >> 2) & 1);
    p1_centre(c, acc, asf(e0.x), asf(e1.x));
    if (w == 0) asm volatile("bar.arrive 7, 256;" ::: "memory");
    e0.y &= ~255u; e1.y &= ~255u;
    ev[0] = asf(e0.y); ev[1] = asf(e1.y);
    ev[2] = asf(kp.y & ~255u); ev[3] = asf(kp.w & ~255u);
    ev[4] = asf(__shfl_sync(0xffffffffu, e0.y, 8 * q)); ev[5] = asf(__shfl_sync(0xffffffffu, e0.y, 8 * q + 4));
    ev[6] = asf(__shfl_sync(0xffffffffu, e1.y, 8 * q)); ev[7] = asf(__shfl_sync(0xffffffffu, e1.y, 8 * q + 4));
    const bool defer = !((tile >> 24) & 1);
    tile_end(c);
    ti++;
    uint32_t lo[24], hi[24];
    p1_park(c, acc, lo, hi, g, tile);
    if (defer) {
      k = DEF_A;
      if (t_type(next)) {
        p1_attention<256>(c, acc, lo, hi, ev, tile);
        tile = next;
        k = DEF_AW;
        goto started;
      }
      p1_attention<192>(c, acc, lo, hi, ev, tile);
      tile = next;
      goto again192;
    }
    p1_attention<0>(c, acc, lo, hi, ev, tile);
    tile = next;
  }
fresh:
  if (tile == TILE_END) goto done;
  k = 1;
  if (t_type(tile) == 0) {
    mma_step<192, true>(c, acc);
  again192:
#pragma unroll
    for (int i = 0; i < 8; i++) cs[i] = 0;
    goto started192;
  }
  mma_step<256, true>(c, acc);
started:
  {
    const uint32_t next = __shfl_sync(0xffffffffu, sched[ti + 1], 0);
    mma_run<256>(c, acc, k, t_nk(tile) - TAIL);
    RowMeans means;
    row_means_load(means, c, tile);
    if (next == TILE_END) c.empty_r = 0;
    const bool geglu = t_type(tile) == 2;
    if (!geglu && ((tile >> 24) & 1)) {
      const bool last = next == TILE_END;
      mbar_spin(sb + (last ? B_GATE : B_COPY), 0);
      out_acquire(c, 0);
      out_acquire(c, 1);
      float left[64], right[64];
      wg_wait<0>();
      release_prev(c);
      c.prev = NSTAGE;
#pragma unroll
      for (int i = 0; i < 64; i++) asm volatile("add.f32 %0, %1, 0f80000000;" : "=f"(left[i]) : "f"(acc[i]));
      if (w == 1) asm volatile("bar.sync 7, 256;" ::: "memory");
      mma_half<0>(c, left, 0, TAIL);
      asm volatile("bar.arrive %0, 256;" :: "r"(7 - w) : "memory");
      row_means_finish(means, c, tile, ev);
      const float m0 = bf_lo(asu(ev[0])), m1 = bf_lo(asu(ev[1]));
#pragma unroll
      for (int i = 0; i < 64; i++) asm volatile("add.f32 %0, %1, %2;" : "=f"(right[i]) : "f"(acc[64 + i]), "f"(i & 2 ? m1 : m0));
      const int col = t_idx(tile) * 256, row = (t_mp(tile) * 2 + rank) * 128 + (g - 1) * 16;
      const uint32_t mine = sb + OFF_STG + w * 8192 + (g - 1) * 2048;
      wg_wait<0>();
      half_out<0, true>(p, c, left, ev, true, mine, col, row);
      asm volatile("bar.sync %0, 256;" :: "r"(6 - w) : "memory");
      mma_half<1>(c, right, 0, 1);
      sched_fence(sb);
      half_out<1, true>(p, c, left, ev, true, mine, col, row);
      bulk_commit();
      mma_half<1>(c, right, 1, TAIL);
      if (w == 0) asm volatile("bar.arrive 5, 256;" ::: "memory");
      bulk_wait_all();
      mbar_arrive_warp(sb + B_HALF);
      tile_end(c);
      release_tail(c, (tile >> 25) & w);
      const bool own = last || w == 0;
      half_out<0, false>(p, c, right, ev, own, mine, col + 128, row);
      half_out<1, false>(p, c, right, ev, own, mine, col + 128, row);
      if (own) {
        bulk_commit();
        bulk_wait_all();
        if (last) goto done;
        mbar_arrive_warp(sb + B_OUTF);
        mbar_arrive_warp(sb + B_OUTF + 8);
      }
      ti++;
      tile = next;
      goto fresh;
    }
    uint32_t r0 = 0, r1 = 0;
    const bool late = (tile >> 30) & 1;
    if (geglu && !late) {
      const uint32_t* hrs = g_hrs + first_row(c, tile);
      r0 = ld_gpu32<0>(hrs); r1 = ld_gpu32<32>(hrs);
    }
#pragma unroll 1
    for (int i = TAIL; i > 0; i--) {
      if (i == 2) stagger_wait(c);
      mma_step<256>(c, acc);
    }
    if (w == 0) asm volatile("bar.arrive 7, 256;" ::: "memory");
    if (geglu) {
      if (late) {
        const uint32_t* hrs = g_hrs + first_row(c, tile);
        r0 = ld_gpu32<0>(hrs); r1 = ld_gpu32<32>(hrs);
      }
    } else {
      row_means_finish(means, c, tile, ev);
    }
    const bool defer = !((tile >> 24) & 1);
    const uint32_t parked = tile;
    tile_end(c);
    ti++;
#pragma unroll
    for (int i = 0; i < 64; i++) pk[i] = pack2(acc[2 * i], acc[2 * i + 1]);
    tile = next;
    if (defer) { mma_step<256, true>(c, acc); sched_fence(sb); }
    if (!geglu) {
      r_chunk<0>(c, pk, ev);
#define F(C) mma_step<256>(c, acc); sched_fence(sb); r_chunk<C>(c, pk, ev);
      F(1) F(2) F(3)
#undef F
      k = DEF_R;
      goto started;
    }
    k = DEF_G;
    if (defer && ((parked >> 30) & 1)) { mma_step<256>(c, acc); sched_fence(sb); k++; }
    {
      const uint32_t tag = lds32(sb + M_EPOCH);
      while (true) {
        if (!__any_sync(0xffffffffu, (((r0 ^ tag) | (r1 ^ tag)) & 255) != 0)) break;
        const uint32_t* hrs = g_hrs + first_row(c, parked);
        r0 = ld_gpu32<0>(hrs); r1 = ld_gpu32<32>(hrs);
      }
      ev[0] = untagged(r0); ev[1] = untagged(r1);
    }
    g_chunk<0>(c, pk, ev);
#define F(C) if (defer) { mma_step<256>(c, acc); sched_fence(sb); } g_chunk<C>(c, pk, ev);
    F(1) F(2) F(3) F(4) F(5) F(6) F(7)
#undef F
    if (defer) goto started;
    wg_wait<0>();
    goto fresh;
  }
done:;
}

__device__ __forceinline__ uint32_t get_epoch(uint32_t sb) {
  mbar_wait(sb + B_EPOCH, 0);
  return lds32(sb + M_EPOCH);
}
__device__ __forceinline__ bool flag_set(bool seen, const uint32_t* flag, uint32_t target) {
  uint32_t v = target;
  asm volatile("{\n.reg .pred p;\nsetp.eq.u32 p, %2, 0;\n@p ld.acquire.gpu.global.u32 %0, [%1];\n}" : "+r"(v) : "l"(flag), "r"((uint32_t)seen) : "memory");
  return (int32_t)(v - target) >= 0;
}

__device__ __forceinline__ void watcher(const Params& p, uint32_t sb, int pair) {
  const uint32_t* sched = p.sched + pair * MAXT;
  const int l = threadIdx.x & 31;
  const uint32_t target = get_epoch(sb) * 32;
  uint32_t base = 0;
  for (int ti = 1;; ti++) {
    const uint32_t tile = __shfl_sync(0xffffffffu, sched[ti], 0);
    if (tile == TILE_END) break;
    const int ty = t_type(tile);
    if (ty == 0) continue;
    const int n = t_deps(tile, t_nk(tile));
    const uint32_t* flag = g_flags + FL_OUT + ((ty - 1) * 8 + t_mp(tile)) * 32 + (t_k0(tile) >> t_sh(tile)) + l;
    bool ok = l >= n;
    int seen = 0;
    while (true) {
      ok = flag_set(ok, flag, target);
      const int lead = __ffs(~__ballot_sync(0xffffffffu, ok) | 0x80000000u) - 1, now = min(lead, n);
      if (now > seen) {
        asm volatile("{\n.reg .pred p;\nsetp.ne.u32 p, %2, 0;\n@p red.relaxed.cluster.shared::cluster.max.u32 [%0], %1;\n}"
                     :: "r"(mapa(sb + M_DEP, (blockIdx.x ^ l) & 1)), "r"(base + now), "r"((uint32_t)(l < (ty == 3 ? 1 : 2))) : "memory");
        seen = now;
        if (now == n) break;
      } else {
        __nanosleep(FLAG_SLEEP);
      }
    }
    base += n;
  }
}

__device__ __forceinline__ void load_stage(uint32_t bar, uint32_t bytes, uint32_t b, const CUtensorMap* tb, int b0, int b1, int b2,
                                           uint32_t a, const CUtensorMap* ta, int a0, int a1, int a2) {
  asm volatile("{\n.reg .pred p;\nelect.sync _|p, 0xffffffff;\n@p mbarrier.arrive.expect_tx.shared::cta.b64 _, [%0], %1;\n"
               "@p cp.async.bulk.tensor.3d.shared::cluster.global.mbarrier::complete_tx::bytes.multicast::cluster [%2], [%3, {%4, %5, %6}], [%0], %12;\n"
               "@p cp.async.bulk.tensor.3d.shared::cluster.global.mbarrier::complete_tx::bytes [%7], [%8, {%9, %10, %11}], [%0];\n}"
               :: "r"(bar), "r"(bytes), "r"(b), "l"(tb), "r"(b0), "r"(b1), "r"(b2), "r"(a), "l"(ta), "r"(a0), "r"(a1), "r"(a2), "h"((uint16_t)3)
               : "memory");
}

__device__ __forceinline__ void mbar_arrive_if(uint32_t bar) {
  asm volatile("{\n.reg .pred p, q;\nelect.sync _|p, 0xffffffff;\nsetp.ne.and.u32 q, %0, 0, p;\n@q mbarrier.arrive.shared::cta.b64 _, [%0];\n}" :: "r"(bar) : "memory");
}

__device__ __forceinline__ void producer(const Params& p, uint32_t sb, int rank, int pair) {
  const uint32_t* sched = p.sched + pair * MAXT;
  uint32_t n = 1, base = 0;
  mbar_arrive_warp(sb + B_EMPTY);
  for (int ti = 0;; ti++) {
    const uint32_t tile = __shfl_sync(0xffffffffu, sched[ti], 0);
    if (tile == TILE_END) break;
    const int ty = t_type(tile), mp = t_mp(tile), idx = t_idx(tile), nk = t_nk(tile), sh = t_sh(tile);
    const int k0 = ty ? t_k0(tile) : p1_k(mp, 0), kmask = ty ? 63 : 15;
    const CUtensorMap* ta = &p.tm[ty == 0 ? TM_X1 : TM_ATTN_A - 1 + ty];
    const CUtensorMap* tb = &p.tm[ty == 0 ? TM_WQKV : ty == 1 ? TM_WO : ty == 3 ? TM_WD : rank ? TM_WU : TM_WG];
    const int a1 = ty ? (mp * 2 + rank) * 128 : mp * 128, a2 = ty ? 0 : rank;
    const int b0 = ty ? 0 : idx * 64, b1 = ty ? 0 : rank * 32, b2 = ty == 0 ? 0 : ty == 2 ? idx * 2 : idx * 4 + rank * 2;
    const uint32_t boff = A_BYTES + rank * (ty ? 16384 : 12288), bytes = ty ? STAGE_BYTES : 40960;
    if (ty) mbar_wait(sb + B_ROWDONE, 0);
    const bool duty = (tile >> 26) & 1;
    int ka = ti == 0, kb = ka;
    const uint32_t n0 = n - ka;
    while (true) {
      int avail = nk;
      if (ty) {
        uint32_t known;
        asm volatile("ld.acquire.cta.shared.u32 %0, [%1];" : "=r"(known) : "r"(sb + M_DEP) : "memory");
        avail = min(nk, (((k0 >> sh) + (int)(__shfl_sync(0xffffffffu, known, 0) - base)) << sh) - k0);
        fence_async_all();
      }
#pragma unroll 1
      for (; ka < min(kb, avail); ka++) {
        const uint32_t st = (n0 + ka) & 3;
        asm volatile("{\n.reg .pred p;\nelect.sync _|p, 0xffffffff;\n"
                     "@p cp.async.bulk.tensor.3d.shared::cluster.global.mbarrier::complete_tx::bytes [%0], [%1, {%3, %4, %5}], [%2];\n}"
                     :: "r"(sb + st * STAGE_BYTES), "l"(ta), "r"(sb + B_FULL + 8 * st), "r"(((k0 + ka) & kmask) * 64), "r"(a1), "r"(a2) : "memory");
      }
#pragma unroll 1
      for (; kb < avail; n++) {
        const uint32_t st = n & 3, dst = sb + st * STAGE_BYTES;
        const int kc = ((k0 + kb) & kmask) * 64;
        mbar_wait(sb + B_EMPTY + 8 * st, ((n >> 2) & 1) ^ 1);
        load_stage(sb + B_FULL + 8 * st, bytes, dst + boff, tb, b0, kc + b1, b2, dst, ta, kc, a1, a2);
        mbar_arrive_if(!duty ? sb + B_EMPTY + 8 * st : kb == 3 ? sb + B_DUTY : 0u);
        ka = ++kb;
      }
      if (ka == nk) break;
      const uint32_t st = n & 3;
      if (kb < nk && kb - ka < (ka ? NSTAGE - 1 : NSTAGE) && mbar_test(sb + B_EMPTY + 8 * st, ((n >> 2) & 1) ^ 1)) {
        asm volatile("{\n.reg .pred p;\nelect.sync _|p, 0xffffffff;\n@p mbarrier.arrive.expect_tx.shared::cta.b64 _, [%0], %1;\n"
                     "@p cp.async.bulk.tensor.3d.shared::cluster.global.mbarrier::complete_tx::bytes.multicast::cluster [%2], [%3, {%4, %5, %6}], [%0], %7;\n}"
                     :: "r"(sb + B_FULL + 8 * st), "r"(bytes), "r"(sb + st * STAGE_BYTES + boff), "l"(tb), "r"(b0), "r"(((k0 + kb) & kmask) * 64 + b1), "r"(b2),
                        "h"((uint16_t)3) : "memory");
        mbar_arrive_if(!duty ? sb + B_EMPTY + 8 * st : kb == 3 ? sb + B_DUTY : 0u);
        kb++;
        n++;
      } else {
        __nanosleep(20);
      }
    }
    if (ty) base += t_deps(tile, nk);
  }
}

template <int PITCH>
__device__ __forceinline__ void rows_g2s(uint32_t dst, const void* src, uint32_t bar) {
  asm volatile("{\n.reg .pred p;\nelect.sync _|p, 0xffffffff;\n@p mbarrier.arrive.expect_tx.shared::cta.b64 _, [%2], 8192;\n"
               "@p cp.async.bulk.shared::cluster.global.mbarrier::complete_tx::bytes [%0], [%1], 2048, [%2];\n"
               "@p cp.async.bulk.shared::cluster.global.mbarrier::complete_tx::bytes [%0 + 2048], [%1 + %3], 2048, [%2];\n"
               "@p cp.async.bulk.shared::cluster.global.mbarrier::complete_tx::bytes [%0 + 4096], [%1 + %4], 2048, [%2];\n"
               "@p cp.async.bulk.shared::cluster.global.mbarrier::complete_tx::bytes [%0 + 6144], [%1 + %5], 2048, [%2];\n}"
               :: "r"(dst), "l"(src), "r"(bar), "n"(PITCH), "n"(2 * PITCH), "n"(3 * PITCH) : "memory");
}
__device__ __forceinline__ void sum_sq8(const uint4& v, float& s, float& qq) {
  const float a0 = bf_lo(v.x), b0 = bf_hi(v.x), a1 = bf_lo(v.y), b1 = bf_hi(v.y), a2 = bf_lo(v.z), b2 = bf_hi(v.z), a3 = bf_lo(v.w), b3 = bf_hi(v.w);
  s += ((a0 + b0) + (a1 + b1)) + ((a2 + b2) + (a3 + b3));
  qq += fmaf(a0, a0, fmaf(b0, b0, fmaf(a1, a1, b1 * b1))) + fmaf(a2, a2, fmaf(b2, b2, fmaf(a3, a3, b3 * b3)));
}
__device__ __forceinline__ float inv_std(float s, float qq) {
  const float mu = s * (1.f / DM);
  return rsqrtf(fmaxf(qq * (1.f / DM) - mu * mu, 0.f) + 1e-5f);
}

__device__ __forceinline__ void x_rows(const Params& p, uint32_t sb, int w) {
  const int l = threadIdx.x & 31;
  if (blockIdx.x < 128) {
    const int row0 = blockIdx.x * 8 + w;
    const uint32_t bar = sb + B_ROW + 16 * w;
    uint32_t reg = sb + (2 * w + 1) * STAGE_BYTES - 8192;
    mbar_wait(sb + B_GO, 0);
    rows_g2s<4096>(reg, p.x + (size_t)row0 * DM, bar);
    const uint32_t tag = get_epoch(sb);
#pragma unroll 1
    for (int pass = 0; pass < 2; pass++) {
      mbar_wait(bar + 8 * pass, 0);
      float s = 0.f, qq = 0.f;
      const uint32_t src = reg + (l >> 3) * 2048 + (l & 7) * 16;
#pragma unroll 1
      for (int u = 0; u < 2048; u += 512) {
        if (pass == 0 && u == 1024) rows_g2s<4096>(reg + STAGE_BYTES, p.x + (size_t)(1024 + row0) * DM, bar + 8);
        uint4 v[4];
#pragma unroll
        for (int i = 0; i < 4; i++) v[i] = lds128(src + u + i * 128);
        sched_fence(sb);
#pragma unroll
        for (int i = 0; i < 4; i++) sum_sq8(v[i], s, qq);
      }
#pragma unroll
      for (int o = 1; o < 8; o <<= 1) { s += __shfl_xor_sync(0xffffffffu, s, o); qq += __shfl_xor_sync(0xffffffffu, qq, o); }
      const int o = w * 1024 + pass * 512 + blockIdx.x * 4 + (l >> 3);
      st_gpu64_if((l & 7) == 0, g_xst + 8 + o, asu(s * (1.f / DM)), tagged(inv_std(s, qq), tag));
#pragma unroll 1
      for (int i = 0; i < 4; i++) {
        asm volatile("{\n.reg .pred p;\nelect.sync _|p, 0xffffffff;\n@p cp.async.bulk.global.shared::cta.bulk_group [%0], [%1], 2048;\n}"
                     :: "l"(p.out + (size_t)(pass * 1024 + row0 + 2 * i) * DM), "r"(reg + i * 2048) : "memory");
        bulk_commit();
        bulk_wait_read<0>();
      }
      reg += STAGE_BYTES;
    }
    bulk_wait_all();
  }
  __syncwarp();
  asm volatile("{\n.reg .pred p;\nsetp.lt.u32 p, %1, 2;\n@p mbarrier.arrive.shared::cluster.b64 _, [%0];\n}"
               :: "r"(mapa(sb + B_ROWDONE, l & 1)), "r"(l) : "memory");
}

__device__ __forceinline__ void wo_rows(const Params& p, uint32_t sb, uint32_t tag) {
  const int l = threadIdx.x & 31, row = l >> 2;
  mbar_wait(sb + B_GO + 8, 0);
  rows_g2s<2048>(sb + OFF_STG + 8192, p.wo + (size_t)blockIdx.x * 8 * DM, sb + B_ROW + 32);
  rows_g2s<2048>(sb + OFF_STG + 24576, p.wo + (size_t)(blockIdx.x * 8 + 4) * DM, sb + B_ROW + 32);
  mbar_wait(sb + B_ROW + 32, 0);
  const uint32_t src = sb + OFF_STG + 8192 + (row >> 2) * 16384 + (row & 3) * 2048 + (row & 1) * 64 + (l & 3) * 16;
  float s = 0.f;
#pragma unroll 1
  for (int u = 0; u < 2048; u += 256) {
    const uint4 v[4] = {lds128(src + u), lds128((src ^ 64) + u), lds128(src + u + 128), lds128((src ^ 64) + u + 128)};
    sched_fence(sb);
#pragma unroll
    for (int i = 0; i < 4; i++) {
      const uint32_t a = add2(v[i].x, v[i].y), b = add2(v[i].z, v[i].w);
      s += (bf_lo(a) + bf_hi(a)) + (bf_lo(b) + bf_hi(b));
    }
  }
  s = quad_sum(s);
  st_gpu64_if((l & 3) == 0, g_rm + blockIdx.x * 8 + row, asu(s * (1.f / DM)), tag);
}

__device__ __forceinline__ void aux_warp(const Params& p, uint32_t sb, int rank, int pair) {
  const int l = threadIdx.x & 31;
  const uint32_t ep = get_epoch(sb);
  mbar_wait(sb + B_ROWDONE, 0);
  if (blockIdx.x < 128) flag_add(l ? nullptr : g_flags + FL_COPY, 1);
  while (true) {
    if (__all_sync(0xffffffffu, flag_set(false, g_flags + FL_COPY, ep * 128))) break;
    __nanosleep(200);
  }
  fence_async_all();
  mbar_arrive_warp(sb + B_COPY);
  const uint32_t* sched = p.sched + pair * MAXT;
  uint32_t n = 0, ph = 0;
  for (int ti = 0;; ti++) {
    const uint32_t tile = __shfl_sync(0xffffffffu, sched[ti], 0);
    if (tile == TILE_END) break;
    if ((tile >> 26) & 1) {
      const int wide = (tile >> 23) & 1, row = ((tile >> 27) & 7) * 16 + (l >> (1 - wide));
      const uint32_t src = sb + row * 128, half = wide ? (row >> 2) & 1 : l & 1;
      float s = 0.f, qq = 0.f;
      mbar_wait(sb + B_DUTY, ph);
      ph ^= 1;
#pragma unroll 1
      for (uint32_t k = n; k < n + 16; k++) {
        const uint32_t st = k & 3;
        mbar_wait(sb + B_FULL + 8 * st, (k >> 2) & 1);
#pragma unroll 1
        for (int j = wide; j >= 0; j--) {
          uint4 v[4];
#pragma unroll
          for (int i = 0; i < 4; i++) v[i] = lds128(src + st * STAGE_BYTES + (half ^ j) * 64 + (((i + row) & 3) << 4));
          mbar_arrive_if(j ? 0u : sb + B_EMPTY + 8 * st);
#pragma unroll
          for (int i = 0; i < 4; i++) {
            const uint32_t t = fma2(v[i].w, v[i].w, fma2(v[i].z, v[i].z, fma2(v[i].y, v[i].y, mul2(v[i].x, v[i].x))));
            s += bf_lo(t); qq += bf_hi(t);
          }
        }
      }
      qq += s;
      if (!wide) qq += __shfl_xor_sync(0xffffffffu, qq, 1);
      st_gpu32_if(wide || !(l & 1), g_hrs + (t_mp(tile) * 2 + rank) * 128 + row, tagged(inv_std(0.f, qq), ep));
    }
    n += t_nk(tile);
  }
}

__device__ __forceinline__ void io_warp(const Params& p, uint32_t sb, int rank, int pair) {
  const uint32_t* sched = p.sched + pair * MAXT;
  const int l = threadIdx.x & 31;
  uint32_t phb = 0;
  uint32_t steps = 0;
  const uint32_t ep = get_epoch(sb);
  if (blockIdx.x < 128) wo_rows(p, sb, ep);
  for (int ti = 0;; ti++) {
    const uint32_t tile = __shfl_sync(0xffffffffu, sched[ti], 0);
    if (tile == TILE_END) break;
    const int ty = t_type(tile), mp = t_mp(tile), idx = t_idx(tile);
    if (ty == 0) {
      if (ti == 0) {
        const uint4* src = (const uint4*)(g_rm + idx * 64) + l;
        uint4 e;
        while (true) {
          e = ld_gpu128(src);
          if (!__any_sync(0xffffffffu, e.y != ep || e.w != ep)) break;
          __nanosleep(100);
        }
        const uint32_t dst = sb + M_RM + (l >> 4) * 128 + (l & 3) * 32 + ((l >> 2) & 3) * 4;
        asm volatile("st.shared.u32 [%0], %1;\nst.shared.u32 [%0 + 16], %2;" :: "r"(dst), "r"(e.x), "r"(e.z) : "memory");
        mbar_arrive_warp(sb + B_RM);
      }
      uint4* box = g_halo + ((mp * 2 - 2 + rank) * 16 + idx) * 128 + l;
      uint4 v[4];
#pragma unroll
      for (int i = 0; i < 4; i++) v[i] = make_uint4(~0u, ~0u, ~0u, ~0u);
      if (mp) {
        while (true) {
          uint32_t least = ~0u;
#pragma unroll
          for (int i = 0; i < 4; i++) v[i] = ld_gpu128(box + i * 32);
#pragma unroll
          for (int i = 0; i < 4; i++) least = min(min(least, min(v[i].x, v[i].y)), min(v[i].z, v[i].w));
          if (!__any_sync(0xffffffffu, least == 0)) break;
          mbar_wait(sb + B_CS, (phb >> 2) & 1);
        }
      }
      phb ^= 4;
#pragma unroll
      for (int i = 0; i < 4; i++) stsm4(sb + OFF_STG + i * 512 + l * 16, ~v[i].x, ~v[i].y, ~v[i].z, ~v[i].w);
      mbar_arrive_warp(sb + B_HALO);
#pragma unroll
      for (int i = 0; i < 4; i++) st_gpu128_if(mp, box + i * 32, 0u, 0u, 0u, 0u);
    } else if (ty == 1) {
      mbar_wait(sb + B_COPY, 0);
    } else if (ty == 3) {
      const uint32_t* flag = g_flags + FL_OUT + (16 + mp) * 32 + l;
      bool ok = l >= 28;
      while (true) {
        ok = flag_set(ok, flag, ep * 32);
        if (__all_sync(0xffffffffu, ok)) break;
        __nanosleep(FLAG_SLEEP);
      }
      fence_async_all();
      if (sched[ti + 1] == TILE_END) {
        mbar_arrive_warp(sb + B_GATE);
        break;
      }
    }
    const int split = (tile >> 24) & ty & 1;
    const bool early = (tile >> 25) & 1;
    const int n = ty == 0 ? 2 : ty == 2 ? 4 : 8, col0 = idx * (n * 32), row0 = ty == 0 ? mp * 128 : (mp * 2 + rank) * 128;
    uint32_t* done = g_flags + FL_OUT + (ty * 8 + mp) * 32 + (ty == 1 ? idx * 2 + 1 : idx);
    const CUtensorMap* tm = &p.tm[ty == 0 ? TM_ATTN_ST : ty == 2 ? TM_ACT_ST : TM_OUT_ST];
    uint32_t before = 0;
    steps += t_nk(tile);
    if (split) {
      mbar_wait(sb + B_HALF, (phb >> 3) & 1);
      phb ^= 8 + 3;
      if (early) flag_add(l ? nullptr : done - 1, t_nk(tile));
    }
#pragma unroll 1
    for (int i = split * 5; i < n; i += 1 + split) {
      const int w = i & 1, ch = i >> 1, sub = ch & 1;
      mbar_wait(sb + B_OUTF + w * 16 + sub * 8, ((phb >> sub) ^ (i >> 2)) & 1);
      const uint32_t src = sb + OFF_STG + w * 16384 + sub * 8192;
      if (ty & 1) tma_add3d(tm, src, col0 + ch * 64, row0 + w * 64, 0);
      else tma_st3d(tm, src, col0 + ch * 64, row0 + w * 64, ty == 0 ? rank : 0);
      bulk_commit();
      bulk_wait_read<1>();
      if (before) mbar_arrive_warp(before);
      before = sb + B_OUTE + w * 16 + sub * 8;
    }
    if (split) {
      mbar_wait(sb + B_OUTF + 8, ((phb >> 1) & 1) ^ 1);
      mbar_arrive_warp(sb + B_OUTE);
      mbar_arrive_warp(sb + B_OUTE + 8);
    }
    phb ^= n == 2 ? 1 : n == 4 ? 3 : 0;
    bulk_wait_all();
    mbar_arrive_warp(before);
    if (ty != 3) flag_add(l == 0 ? done : ty == 1 && l == 1 && !early ? done - 1 : nullptr, t_nk(tile));
    asm volatile("{\n.reg .pred p;\nsetp.ne.u32 p, %1, 0;\n@p mbarrier.arrive.shared::cluster.b64 _, [%0];\n}"
                 :: "r"(mapa(sb + B_EMPTY + 8 * ((steps + 1 + (l >> 1)) & 3), l & 1)), "r"((uint32_t)(early && l < 2 * TAIL)) : "memory");
  }
}

__global__ void __cluster_dims__(2, 1, 1) __launch_bounds__(384, 1) fused_block_kernel(const __grid_constant__ Params p) {
  extern __shared__ __align__(1024) uint8_t smem_raw[];
  uint32_t sb = (uint32_t)__cvta_generic_to_shared(smem_raw);
  asm volatile("" : "+r"(sb));
  sb = __shfl_sync(0xffffffffu, sb, 0);
  const int wg = __shfl_sync(0xffffffffu, threadIdx.x >> 7, 0);
  const int rank = __shfl_sync(0xffffffffu, blockIdx.x & 1, 0), pair = __shfl_sync(0xffffffffu, blockIdx.x >> 1, 0);
  const int warp = __shfl_sync(0xffffffffu, threadIdx.x >> 5, 0) - 8;
  if (warp == 0) {
    const uint32_t t0 = (pair >> 4) << 2 | (pair & 15) << 5;
    const int kc = p1_k(t_mp(t0), 0) * 64;
    asm volatile("{\n.reg .pred p;\nelect.sync _|p, 0xffffffff;\n"
                 "@p mbarrier.init.shared::cta.b64 [%0], 1;\nfence.mbarrier_init.release.cluster;\nfence.proxy.async.shared::cta;\n"
                 "@p mbarrier.arrive.expect_tx.shared::cta.b64 _, [%0], 40960;\n"
                 "@p cp.async.bulk.tensor.3d.shared::cluster.global.mbarrier::complete_tx::bytes [%1 + 16384], [%2, {%4, %5, %9}], [%0];\n"
                 "@p cp.async.bulk.tensor.3d.shared::cluster.global.mbarrier::complete_tx::bytes [%1], [%3, {%5, %7, %8}], [%0];\n"
                 "@p cp.async.bulk.tensor.3d.shared::cluster.global.mbarrier::complete_tx::bytes [%1 + 28672], [%2, {%4, %6, %9}], [%0];\n}"
                 :: "r"(sb + B_FULL), "r"(sb), "l"(&p.tm[TM_WQKV]), "l"(&p.tm[TM_X1]), "r"(t_idx(t0) * 64), "r"(kc), "r"(kc + 32),
                    "r"(t_mp(t0) * 128), "r"(rank), "r"(0) : "memory");
  }
  if (threadIdx.x == 0) {
#pragma unroll
    for (int i = 0; i < 4; i++) {
      if (i) mbar_init(sb + B_FULL + 8 * i, 1);
      mbar_init(sb + B_EMPTY + 8 * i, 5); mbar_init(sb + B_OUTF + 8 * i, 4); mbar_init(sb + B_OUTE + 8 * i, 1); mbar_init(sb + B_ROW + 8 * i, 1);
    }
    mbar_init(sb + B_HALO, 4); mbar_init(sb + B_HALO + 8, 4); mbar_init(sb + B_RM, 1); mbar_init(sb + B_EPOCH, 1);
    mbar_init(sb + B_CS, 8); mbar_init(sb + B_ROWDONE, 4); mbar_init(sb + B_ROW + 32, 2); mbar_init(sb + B_GATE, 1); mbar_init(sb + B_COPY, 1); mbar_init(sb + B_DUMP, 8); mbar_init(sb + B_HALF, 8);
    mbar_init(sb + B_GO, 8); mbar_init(sb + B_GO + 8, 8); mbar_init(sb + B_DUTY, 1);
    asm volatile("st.shared.u32 [%0], %1;" :: "r"(sb + M_DEP), "r"(0) : "memory");
    asm volatile("fence.mbarrier_init.release.cluster;" ::: "memory");
    fence_async_smem();
  }
  if (threadIdx.x >= 32 && threadIdx.x < 56) asm volatile("st.shared.u32 [%0], %1;" :: "r"(sb + M_CS + 640 + threadIdx.x * 4), "r"(0) : "memory");
  __syncthreads();
  asm volatile("barrier.cluster.arrive.relaxed.aligned;\nbarrier.cluster.wait.aligned;" ::: "memory");
  if (wg < 2) {
    asm volatile("setmaxnreg.inc.sync.aligned.u32 224;");
    consumer(p, sb, wg, rank, pair);
  } else {
    asm volatile("setmaxnreg.dec.sync.aligned.u32 56;");
    if (warp > 0) {
      if (threadIdx.x == 289) {
        const uint32_t e = atomicAdd(g_flags + FL_LAUNCH, 1u) / (uint32_t)p.ncta + 1;
        asm volatile("st.shared.u32 [%0], %1;" :: "r"(sb + M_EPOCH), "r"(e) : "memory");
        mbar_arrive(sb + B_EPOCH);
#pragma unroll
        for (int i = TM_ATTN_ST; i < TM_COUNT; i++) asm volatile("prefetch.tensormap [%0];" :: "l"(&p.tm[i]) : "memory");
      }
      __syncwarp();
      if (warp == 1) {
        io_warp(p, sb, rank, pair);
      } else {
        x_rows(p, sb, warp - 2);
        if (warp == 2) aux_warp(p, sb, rank, pair);
        else watcher(p, sb, pair);
      }
    } else {
      producer(p, sb, rank, pair);
    }
  }
}

typedef CUresult (*EncodeFn)(CUtensorMap*, CUtensorMapDataType, cuuint32_t, void*, const cuuint64_t*, const cuuint64_t*, const cuuint32_t*,
                             const cuuint32_t*, CUtensorMapInterleave, CUtensorMapSwizzle, CUtensorMapL2promotion, CUtensorMapFloatOOBfill);

void encode(EncodeFn fn, CUtensorMap* m, const void* ptr, uint64_t d0, uint64_t d1, uint64_t d2, uint64_t s1, uint64_t s2,
            uint32_t b0, uint32_t b1, uint32_t b2) {
  const cuuint64_t dims[3] = {d0, d1, d2}, strides[2] = {s1, s2};
  const cuuint32_t box[3] = {b0, b1, b2}, es[3] = {1, 1, 1};
  fn(m, CU_TENSOR_MAP_DATA_TYPE_BFLOAT16, 3, (void*)ptr, dims, strides, box, es, CU_TENSOR_MAP_INTERLEAVE_NONE,
     CU_TENSOR_MAP_SWIZZLE_128B, CU_TENSOR_MAP_L2_PROMOTION_L2_128B, CU_TENSOR_MAP_FLOAT_OOB_FILL_NONE);
}

const uint32_t kSchedule[MAXPAIRS * MAXT] = {
  0x01100000, 0x0110001c, 0x00500051, 0x011002c6, 0x7490001e, 0x0010031e, 0x004d6417, 0x010a5c07, TILE_END, TILE_END, TILE_END, TILE_END, TILE_END, TILE_END, TILE_END, TILE_END,
  0x01100020, 0x0010003c, 0x40100062, 0x401000ee, 0x74100092, 0x00100176, 0x01190017, TILE_END, TILE_END, TILE_END, TILE_END, TILE_END, TILE_END, TILE_END, TILE_END, TILE_END,
  0x01100040, 0x0010005c, 0x7c100102, 0x4010032e, 0x6c100216, 0x00100116, 0x011a006b, TILE_END, TILE_END, TILE_END, TILE_END, TILE_END, TILE_END, TILE_END, TILE_END, TILE_END,
  0x01100060, 0x0010007c, 0x40100142, 0x401000ae, 0x6c100232, 0x001001be, 0x011a0077, TILE_END, TILE_END, TILE_END, TILE_END, TILE_END, TILE_END, TILE_END, TILE_END, TILE_END,
  0x01100080, 0x00100098, 0x40100362, 0x401001ce, 0x40100272, 0x001001de, 0x011a7873, TILE_END, TILE_END, TILE_END, TILE_END, TILE_END, TILE_END, TILE_END, TILE_END, TILE_END,
  0x011000a0, 0x001000bc, 0x401000a2, 0x4010034e, 0x40100236, 0x00558c6f, 0x01158c1f, TILE_END, TILE_END, TILE_END, TILE_END, TILE_END, TILE_END, TILE_END, TILE_END, TILE_END,
  0x011000c0, 0x001000dc, 0x40100162, 0x4010006e, 0x401000b2, 0x004cb02f, 0x015e0073, TILE_END, TILE_END, TILE_END, TILE_END, TILE_END, TILE_END, TILE_END, TILE_END, TILE_END,
  0x011000e0, 0x03042001, 0x54100242, 0x00500079, 0x5c100052, 0x00550043, 0x0156885b, TILE_END, TILE_END, TILE_END, TILE_END, TILE_END, TILE_END, TILE_END, TILE_END, TILE_END,
  0x01100100, 0x01043021, 0x03062805, 0x441000e6, 0x5410002a, 0x0010013e, 0x000c0063, 0x0157001f, TILE_END, TILE_END, TILE_END, TILE_END, TILE_END, TILE_END, TILE_END, TILE_END,
  0x01100120, 0x03470021, 0x00500015, 0x00100346, 0x4010029e, 0x00100312, 0x0156005f, TILE_END, TILE_END, TILE_END, TILE_END, TILE_END, TILE_END, TILE_END, TILE_END, TILE_END,
  0x01100140, 0x00100158, 0x401001e2, 0x4010018e, 0x40100096, 0x001002f2, 0x000d5443, 0x010d541b, TILE_END, TILE_END, TILE_END, TILE_END, TILE_END, TILE_END, TILE_END, TILE_END,
  0x01100160, 0x0010017c, 0x40100342, 0x401001ae, 0x401000d2, 0x001001da, 0x000dac43, 0x010d6837, TILE_END, TILE_END, TILE_END, TILE_END, TILE_END, TILE_END, TILE_END, TILE_END,
  0x01100180, 0x03041001, 0x0146280d, 0x4c100106, 0x5c10004a, 0x4c10027a, 0x0010033a, 0x01129817, TILE_END, TILE_END, TILE_END, TILE_END, TILE_END, TILE_END, TILE_END, TILE_END,
  0x011001a0, 0x001001b8, 0x401002c2, 0x4010004e, 0x401001d6, 0x001000ba, 0x000d686b, 0x010d000f, TILE_END, TILE_END, TILE_END, TILE_END, TILE_END, TILE_END, TILE_END, TILE_END,
  0x011001c0, 0x001001d8, 0x401002e2, 0x4010012e, 0x40100256, 0x001002fa, 0x004c002b, 0x010e0067, TILE_END, TILE_END, TILE_END, TILE_END, TILE_END, TILE_END, TILE_END, TILE_END,
  0x011001e0, 0x034a0005, 0x6c100046, 0x7c10012a, 0x0010027e, 0x000f340f, 0x0114907f, TILE_END, TILE_END, TILE_END, TILE_END, TILE_END, TILE_END, TILE_END, TILE_END, TILE_END,
  0x01100004, 0x014c1061, 0x00500055, 0x00100366, 0x4010025e, 0x0165004f, TILE_END, TILE_END, TILE_END, TILE_END, TILE_END, TILE_END, TILE_END, TILE_END, TILE_END, TILE_END,
  0x01100024, 0x01051c21, 0x01072425, 0x64100006, 0x7410000a, 0x5c10013a, 0x0010033e, 0x0113944f, TILE_END, TILE_END, TILE_END, TILE_END, TILE_END, TILE_END, TILE_END, TILE_END,
  0x01100044, 0x01100054, 0x00500011, 0x00100326, 0x5490023e, 0x0010011e, 0x0158007f, TILE_END, TILE_END, TILE_END, TILE_END, TILE_END, TILE_END, TILE_END, TILE_END, TILE_END,
  0x01100064, 0x01100074, 0x00500071, 0x00100306, 0x4490003e, 0x0010031a, 0x01578407, TILE_END, TILE_END, TILE_END, TILE_END, TILE_END, TILE_END, TILE_END, TILE_END, TILE_END,
  0x01100084, 0x0010009c, 0x40100222, 0x4010020e, 0x401000b6, 0x01290003, TILE_END, TILE_END, TILE_END, TILE_END, TILE_END, TILE_END, TILE_END, TILE_END, TILE_END, TILE_END,
  0x001000a4, 0x001000b8, 0x6c100262, 0x6c10000e, 0x64100036, 0x001002d2, 0x0050a04b, 0x010a5057, TILE_END, TILE_END, TILE_END, TILE_END, TILE_END, TILE_END, TILE_END, TILE_END,
  0x001000c4, 0x011000d0, 0x40100122, 0x4010002e, 0x7c100212, 0x00100136, 0x011a0027, TILE_END, TILE_END, TILE_END, TILE_END, TILE_END, TILE_END, TILE_END, TILE_END, TILE_END,
  0x001000e4, 0x011000f0, 0x0105000d, 0x74100126, 0x4010014a, 0x0010007e, 0x00100332, 0x0153943f, TILE_END, TILE_END, TILE_END, TILE_END, TILE_END, TILE_END, TILE_END, TILE_END,
  0x00100104, 0x00100118, 0x0008002d, 0x40100166, 0x4010016a, 0x001000f2, 0x0123302b, TILE_END, TILE_END, TILE_END, TILE_END, TILE_END, TILE_END, TILE_END, TILE_END, TILE_END,
  0x00100124, 0x00100134, 0x0110013c, 0x00100266, 0x44100012, 0x00100356, 0x0110021a, 0x010cb00f, TILE_END, TILE_END, TILE_END, TILE_END, TILE_END, TILE_END, TILE_END, TILE_END,
  0x01100144, 0x0010015c, 0x40100202, 0x401001ee, 0x40100316, 0x001000da, 0x000d004b, 0x010c607f, TILE_END, TILE_END, TILE_END, TILE_END, TILE_END, TILE_END, TILE_END, TILE_END,
  0x00100164, 0x00100178, 0x40100182, 0x7c1002ae, 0x741002b6, 0x00100156, 0x011a0023, TILE_END, TILE_END, TILE_END, TILE_END, TILE_END, TILE_END, TILE_END, TILE_END, TILE_END,
  0x00100184, 0x00100190, 0x00080009, 0x7c1001c6, 0x401001ea, 0x6410023a, 0x00100352, 0x0153943b, TILE_END, TILE_END, TILE_END, TILE_END, TILE_END, TILE_END, TILE_END, TILE_END,
  0x001001a4, 0x001001b0, 0x001001bc, 0x0050003d, 0x0010024a, 0x001002ba, 0x015e6823, TILE_END, TILE_END, TILE_END, TILE_END, TILE_END, TILE_END, TILE_END, TILE_END, TILE_END,
  0x011001c4, 0x03443001, 0x441000c2, 0x4c1002ce, 0x4c100016, 0x00583063, 0x0113007b, TILE_END, TILE_END, TILE_END, TILE_END, TILE_END, TILE_END, TILE_END, TILE_END, TILE_END,
  0x001001e4, 0x001001f4, 0x001001fc, 0x0050005d, 0x0010032a, 0x001002b2, 0x011000fa, 0x010c5c1f, TILE_END, TILE_END, TILE_END, TILE_END, TILE_END, TILE_END, TILE_END, TILE_END,
  0x00100008, 0x01100014, 0x401002a2, 0x4010028e, 0x40100072, 0x001001ba, 0x00519c37, 0x0109002f, TILE_END, TILE_END, TILE_END, TILE_END, TILE_END, TILE_END, TILE_END, TILE_END,
  0x00100028, 0x00100038, 0x00500069, 0x4410022e, 0x44100276, 0x00100376, 0x00529877, 0x01098843, TILE_END, TILE_END, TILE_END, TILE_END, TILE_END, TILE_END, TILE_END, TILE_END,
  0x00100048, 0x00100058, 0x401001c2, 0x4010014e, 0x40100252, 0x00149063, 0x0156881b, TILE_END, TILE_END, TILE_END, TILE_END, TILE_END, TILE_END, TILE_END, TILE_END, TILE_END,
  0x00100068, 0x01100070, 0x40100302, 0x4010036e, 0x401002d6, 0x00100152, 0x011a0037, TILE_END, TILE_END, TILE_END, TILE_END, TILE_END, TILE_END, TILE_END, TILE_END, TILE_END,
  0x00100088, 0x01100094, 0x00500031, 0x011002e6, 0x6490017e, 0x00100172, 0x01170007, TILE_END, TILE_END, TILE_END, TILE_END, TILE_END, TILE_END, TILE_END, TILE_END, TILE_END,
  0x001000a8, 0x001000b4, 0x0008006d, 0x40100146, 0x4010026a, 0x7410015a, 0x004fa403, 0x01140057, TILE_END, TILE_END, TILE_END, TILE_END, TILE_END, TILE_END, TILE_END, TILE_END,
  0x001000c8, 0x001000d4, 0x00482009, 0x401000c6, 0x4010008a, 0x00100292, 0x0010035e, 0x0112005b, TILE_END, TILE_END, TILE_END, TILE_END, TILE_END, TILE_END, TILE_END, TILE_END,
  0x001000e8, 0x001000f4, 0x011000fc, 0x00100286, 0x0010036a, 0x0010019e, 0x015d0033, TILE_END, TILE_END, TILE_END, TILE_END, TILE_END, TILE_END, TILE_END, TILE_END, TILE_END,
  0x00100108, 0x00100110, 0x0048204d, 0x401000a6, 0x4010006a, 0x7c10001a, 0x0123242f, TILE_END, TILE_END, TILE_END, TILE_END, TILE_END, TILE_END, TILE_END, TILE_END, TILE_END,
  0x00100128, 0x00100130, 0x0048206d, 0x401001e6, 0x401000aa, 0x4010007a, 0x0010037e, 0x0112003b, TILE_END, TILE_END, TILE_END, TILE_END, TILE_END, TILE_END, TILE_END, TILE_END,
  0x00100148, 0x00100150, 0x00482065, 0x40100246, 0x401002ea, 0x4010025a, 0x0010037a, 0x0112003f, TILE_END, TILE_END, TILE_END, TILE_END, TILE_END, TILE_END, TILE_END, TILE_END,
  0x00100168, 0x00100174, 0x01080045, 0x01500019, 0x0010022a, 0x00100112, 0x004c000b, 0x0113483b, TILE_END, TILE_END, TILE_END, TILE_END, TILE_END, TILE_END, TILE_END, TILE_END,
  0x00100188, 0x00100194, 0x00080065, 0x40100086, 0x401001aa, 0x0010015e, 0x0010021e, 0x0153947b, TILE_END, TILE_END, TILE_END, TILE_END, TILE_END, TILE_END, TILE_END, TILE_END,
  0x011001a8, 0x03040001, 0x4c100002, 0x5410024e, 0x541001f6, 0x001000f6, 0x011b7433, TILE_END, TILE_END, TILE_END, TILE_END, TILE_END, TILE_END, TILE_END, TILE_END, TILE_END,
  0x001001c8, 0x001001d0, 0x001001dc, 0x00500059, 0x0010030a, 0x001000be, 0x015e6827, TILE_END, TILE_END, TILE_END, TILE_END, TILE_END, TILE_END, TILE_END, TILE_END, TILE_END,
  0x001001e8, 0x001001f8, 0x00080049, 0x40100066, 0x4010028a, 0x6c10005a, 0x0123300b, TILE_END, TILE_END, TILE_END, TILE_END, TILE_END, TILE_END, TILE_END, TILE_END, TILE_END,
  0x0010000c, 0x00100018, 0x0048202d, 0x401001a6, 0x4010018a, 0x4010017a, 0x0010035a, 0x01132853, TILE_END, TILE_END, TILE_END, TILE_END, TILE_END, TILE_END, TILE_END, TILE_END,
  0x0010002c, 0x01100034, 0x401001a2, 0x4010010e, 0x40100076, 0x001002fe, 0x015a7857, TILE_END, TILE_END, TILE_END, TILE_END, TILE_END, TILE_END, TILE_END, TILE_END, TILE_END,
  0x0010004c, 0x01100050, 0x01040061, 0x00500075, 0x441000ea, 0x0010005e, 0x001001fe, 0x0115001b, TILE_END, TILE_END, TILE_END, TILE_END, TILE_END, TILE_END, TILE_END, TILE_END,
  0x0010006c, 0x00100078, 0x40100322, 0x4010016e, 0x401002f6, 0x001000fe, 0x0050700f, 0x010a0053, TILE_END, TILE_END, TILE_END, TILE_END, TILE_END, TILE_END, TILE_END, TILE_END,
  0x0010008c, 0x01100090, 0x40100282, 0x401000ce, 0x401001b6, 0x005a0047, 0x0110485b, TILE_END, TILE_END, TILE_END, TILE_END, TILE_END, TILE_END, TILE_END, TILE_END, TILE_END,
  0x001000ac, 0x011000b0, 0x0105140d, 0x54100026, 0x6c10010a, 0x5410003a, 0x00100192, 0x0113945f, TILE_END, TILE_END, TILE_END, TILE_END, TILE_END, TILE_END, TILE_END, TILE_END,
  0x001000cc, 0x001000d8, 0x641000e2, 0x641002ee, 0x641001f2, 0x00100132, 0x011b7413, TILE_END, TILE_END, TILE_END, TILE_END, TILE_END, TILE_END, TILE_END, TILE_END, TILE_END,
  0x001000ec, 0x001000f8, 0x0008004d, 0x40100186, 0x401001ca, 0x0010009e, 0x0010011a, 0x01124c7b, TILE_END, TILE_END, TILE_END, TILE_END, TILE_END, TILE_END, TILE_END, TILE_END,
  0x0010010c, 0x00100114, 0x0110011c, 0x001002a6, 0x4c100032, 0x0010009a, 0x015d0013, TILE_END, TILE_END, TILE_END, TILE_END, TILE_END, TILE_END, TILE_END, TILE_END, TILE_END,
  0x0010012c, 0x00100138, 0x00482049, 0x40100226, 0x401002ca, 0x00100336, 0x001001b2, 0x0113483f, TILE_END, TILE_END, TILE_END, TILE_END, TILE_END, TILE_END, TILE_END, TILE_END,
  0x0010014c, 0x00100154, 0x01482045, 0x0150001d, 0x0010020a, 0x001000d6, 0x00100372, 0x010f585f, TILE_END, TILE_END, TILE_END, TILE_END, TILE_END, TILE_END, TILE_END, TILE_END,
  0x0010016c, 0x00100170, 0x74100042, 0x7410030e, 0x7c100196, 0x001000de, 0x00519c6b, 0x0109bc0b, TILE_END, TILE_END, TILE_END, TILE_END, TILE_END, TILE_END, TILE_END, TILE_END,
  0x0010018c, 0x00100198, 0x0010019c, 0x00500039, 0x0010034a, 0x0010019a, 0x011e6847, TILE_END, TILE_END, TILE_END, TILE_END, TILE_END, TILE_END, TILE_END, TILE_END, TILE_END,
  0x001001ac, 0x001001b4, 0x5c100022, 0x5c10026e, 0x5c100296, 0x001002da, 0x015b7453, TILE_END, TILE_END, TILE_END, TILE_END, TILE_END, TILE_END, TILE_END, TILE_END, TILE_END,
  0x001001cc, 0x001001d4, 0x40100082, 0x4010008e, 0x40100056, 0x016a3867, TILE_END, TILE_END, TILE_END, TILE_END, TILE_END, TILE_END, TILE_END, TILE_END, TILE_END, TILE_END,
  0x001001ec, 0x001001f0, 0x00500029, 0x0050007d, 0x541001d2, 0x001002de, 0x011b344b, TILE_END, TILE_END, TILE_END, TILE_END, TILE_END, TILE_END, TILE_END, TILE_END, TILE_END,
  0x01100010, 0x00040041, 0x01490025, 0x00500035, 0x4c1000ca, 0x001002be, 0x001001fa, 0x000c6877, 0x0109bc2b, TILE_END, TILE_END, TILE_END, TILE_END, TILE_END, TILE_END, TILE_END,
  0x01100030, 0x034c1041, 0x5c100206, 0x641002aa, 0x4410029a, 0x0123006f, TILE_END, TILE_END, TILE_END, TILE_END, TILE_END, TILE_END, TILE_END, TILE_END, TILE_END, TILE_END,
};

int build_schedule(uint32_t* sched) {
  memcpy(sched, kSchedule, sizeof(kSchedule));
  for (int i = 0; i < MAXPAIRS * MAXT; i++) {
    const uint32_t t = sched[i];
    if (t == TILE_END) continue;
    const uint32_t u = sched[i + 1], ty = t & 3;
    if (u == TILE_END || (ty && !(u & 3)) || (int)((u >> 16) & 63) < (ty == 0 ? DEF_AW : ty == 2 ? DEF_G + ((t >> 30) & 1) : DEF_R) + TAIL) sched[i] |= 1u << 24;
  }
  return MAXPAIRS;
}

}

extern "C" void kernel_launch(void* const* d_in, const int* in_sizes, int n_in, void* d_out, int out_size) {
  static Params p;
  static void* seen[7];
  if (p.out != d_out || memcmp(seen, d_in, sizeof(seen))) {
    memcpy(seen, d_in, sizeof(seen));
    void* fnp = nullptr;
    cudaDriverEntryPointQueryResult qr;
    cudaGetDriverEntryPoint("cuTensorMapEncodeTiled", &fnp, cudaEnableDefault, &qr);
    EncodeFn fn = (EncodeFn)fnp;
    p.x = (const __nv_bfloat16*)d_in[0];
    p.wo = (const __nv_bfloat16*)d_in[2];
    p.out = (__nv_bfloat16*)d_out;
    void *attn, *act;
    cudaGetSymbolAddress(&attn, g_attn);
    cudaGetSymbolAddress(&act, g_act);
    encode(fn, &p.tm[TM_X1], p.x, DM, S_LEN / 2, 2, DM * 4, DM * 2, 64, 128, 1);
    encode(fn, &p.tm[TM_ATTN_ST], attn, DM, S_LEN / 2, 2, DM * 4, DM * 2, 64, 64, 1);
    encode(fn, &p.tm[TM_ATTN_A], attn, DM, S_LEN, 1, DM * 2, S_LEN * DM * 2, 64, 128, 1);
    encode(fn, &p.tm[TM_H_A], d_out, DM, S_LEN, 1, DM * 2, S_LEN * DM * 2, 64, 128, 1);
    encode(fn, &p.tm[TM_ACT_A], act, DF, S_LEN, 1, DF * 2, S_LEN * DF * 2, 64, 128, 1);
    encode(fn, &p.tm[TM_OUT16], d_out, DM, S_LEN, 1, DM * 2, S_LEN * DM * 2, 64, 16, 1);
    encode(fn, &p.tm[TM_OUT_ST], d_out, DM, S_LEN, 1, DM * 2, S_LEN * DM * 2, 64, 64, 1);
    encode(fn, &p.tm[TM_ACT_ST], act, DF, S_LEN, 1, DF * 2, S_LEN * DF * 2, 64, 64, 1);
    encode(fn, &p.tm[TM_WQKV], d_in[1], DM, DM, 3, 3 * DM * 2, DM * 2, 64, 32, 3);
    encode(fn, &p.tm[TM_WO], p.wo, 64, DM, DM / 64, DM * 2, 128, 64, 64, 2);
    encode(fn, &p.tm[TM_WG], d_in[4], 64, DM, DF / 64, DF * 2, 128, 64, 64, 2);
    encode(fn, &p.tm[TM_WU], d_in[5], 64, DM, DF / 64, DF * 2, 128, 64, 64, 2);
    encode(fn, &p.tm[TM_WD], d_in[6], 64, DF, DM / 64, DM * 2, 128, 64, 64, 2);
    cudaFuncSetAttribute(fused_block_kernel, cudaFuncAttributeMaxDynamicSharedMemorySize, SMEM_BYTES);
    p.ncta = 2 * build_schedule(p.sched);
  }
  fused_block_kernel<<<p.ncta, 384, SMEM_BYTES>>>(p);
}
```

```cpp
#include <cuda_runtime.h>
#include <cuda_bf16.h>
#include <cuda.h>
#include <stdint.h>
#include <string.h>

template <int N>
__device__ __forceinline__ void wgmma128(float (&d)[N], uint64_t da, uint64_t db) {
  asm volatile("wgmma.mma_async.sync.aligned.m64n128k16.f32.bf16.bf16 "
    "{%0, %1, %2, %3, %4, %5, %6, %7, %8, %9, %10, %11, %12, %13, %14, %15, %16, %17, %18, %19, %20, %21, %22, %23, %24, %25, %26, %27, %28, %29, %30, %31, %32, %33, %34, %35, %36, %37, %38, %39, %40, %41, %42, %43, %44, %45, %46, %47, %48, %49, %50, %51, %52, %53, %54, %55, %56, %57, %58, %59, %60, %61, %62, %63}, %64, %65, 1, 1, 1, 0, 1;"
    : "+f"(d[0]), "+f"(d[1]), "+f"(d[2]), "+f"(d[3]), "+f"(d[4]), "+f"(d[5]), "+f"(d[6]), "+f"(d[7]), "+f"(d[8]), "+f"(d[9]), "+f"(d[10]), "+f"(d[11]), "+f"(d[12]), "+f"(d[13]), "+f"(d[14]), "+f"(d[15]), "+f"(d[16]), "+f"(d[17]), "+f"(d[18]), "+f"(d[19]), "+f"(d[20]), "+f"(d[21]), "+f"(d[22]), "+f"(d[23]), "+f"(d[24]), "+f"(d[25]), "+f"(d[26]), "+f"(d[27]), "+f"(d[28]), "+f"(d[29]), "+f"(d[30]), "+f"(d[31]), "+f"(d[32]), "+f"(d[33]), "+f"(d[34]), "+f"(d[35]), "+f"(d[36]), "+f"(d[37]), "+f"(d[38]), "+f"(d[39]), "+f"(d[40]), "+f"(d[41]), "+f"(d[42]), "+f"(d[43]), "+f"(d[44]), "+f"(d[45]), "+f"(d[46]), "+f"(d[47]), "+f"(d[48]), "+f"(d[49]), "+f"(d[50]), "+f"(d[51]), "+f"(d[52]), "+f"(d[53]), "+f"(d[54]), "+f"(d[55]), "+f"(d[56]), "+f"(d[57]), "+f"(d[58]), "+f"(d[59]), "+f"(d[60]), "+f"(d[61]), "+f"(d[62]), "+f"(d[63])
    : "l"(da), "l"(db));
}
__device__ __forceinline__ void wgmma192(float (&d)[128], uint64_t da, uint64_t db) {
  asm volatile("wgmma.mma_async.sync.aligned.m64n192k16.f32.bf16.bf16 "
    "{%0, %1, %2, %3, %4, %5, %6, %7, %8, %9, %10, %11, %12, %13, %14, %15, %16, %17, %18, %19, %20, %21, %22, %23, %24, %25, %26, %27, %28, %29, %30, %31, %32, %33, %34, %35, %36, %37, %38, %39, %40, %41, %42, %43, %44, %45, %46, %47, %48, %49, %50, %51, %52, %53, %54, %55, %56, %57, %58, %59, %60, %61, %62, %63, %64, %65, %66, %67, %68, %69, %70, %71, %72, %73, %74, %75, %76, %77, %78, %79, %80, %81, %82, %83, %84, %85, %86, %87, %88, %89, %90, %91, %92, %93, %94, %95}, %96, %97, 1, 1, 1, 0, 1;"
    : "+f"(d[0]), "+f"(d[1]), "+f"(d[2]), "+f"(d[3]), "+f"(d[4]), "+f"(d[5]), "+f"(d[6]), "+f"(d[7]), "+f"(d[8]), "+f"(d[9]), "+f"(d[10]), "+f"(d[11]), "+f"(d[12]), "+f"(d[13]), "+f"(d[14]), "+f"(d[15]), "+f"(d[16]), "+f"(d[17]), "+f"(d[18]), "+f"(d[19]), "+f"(d[20]), "+f"(d[21]), "+f"(d[22]), "+f"(d[23]), "+f"(d[24]), "+f"(d[25]), "+f"(d[26]), "+f"(d[27]), "+f"(d[28]), "+f"(d[29]), "+f"(d[30]), "+f"(d[31]), "+f"(d[32]), "+f"(d[33]), "+f"(d[34]), "+f"(d[35]), "+f"(d[36]), "+f"(d[37]), "+f"(d[38]), "+f"(d[39]), "+f"(d[40]), "+f"(d[41]), "+f"(d[42]), "+f"(d[43]), "+f"(d[44]), "+f"(d[45]), "+f"(d[46]), "+f"(d[47]), "+f"(d[48]), "+f"(d[49]), "+f"(d[50]), "+f"(d[51]), "+f"(d[52]), "+f"(d[53]), "+f"(d[54]), "+f"(d[55]), "+f"(d[56]), "+f"(d[57]), "+f"(d[58]), "+f"(d[59]), "+f"(d[60]), "+f"(d[61]), "+f"(d[62]), "+f"(d[63]), "+f"(d[64]), "+f"(d[65]), "+f"(d[66]), "+f"(d[67]), "+f"(d[68]), "+f"(d[69]), "+f"(d[70]), "+f"(d[71]), "+f"(d[72]), "+f"(d[73]), "+f"(d[74]), "+f"(d[75]), "+f"(d[76]), "+f"(d[77]), "+f"(d[78]), "+f"(d[79]), "+f"(d[80]), "+f"(d[81]), "+f"(d[82]), "+f"(d[83]), "+f"(d[84]), "+f"(d[85]), "+f"(d[86]), "+f"(d[87]), "+f"(d[88]), "+f"(d[89]), "+f"(d[90]), "+f"(d[91]), "+f"(d[92]), "+f"(d[93]), "+f"(d[94]), "+f"(d[95])
    : "l"(da), "l"(db));
}
__device__ __forceinline__ void wgmma192_init(float (&d)[128], uint64_t da, uint64_t db) {
  asm volatile("wgmma.mma_async.sync.aligned.m64n192k16.f32.bf16.bf16 "
    "{%0, %1, %2, %3, %4, %5, %6, %7, %8, %9, %10, %11, %12, %13, %14, %15, %16, %17, %18, %19, %20, %21, %22, %23, %24, %25, %26, %27, %28, %29, %30, %31, %32, %33, %34, %35, %36, %37, %38, %39, %40, %41, %42, %43, %44, %45, %46, %47, %48, %49, %50, %51, %52, %53, %54, %55, %56, %57, %58, %59, %60, %61, %62, %63, %64, %65, %66, %67, %68, %69, %70, %71, %72, %73, %74, %75, %76, %77, %78, %79, %80, %81, %82, %83, %84, %85, %86, %87, %88, %89, %90, %91, %92, %93, %94, %95}, %96, %97, 0, 1, 1, 0, 1;"
    : "=f"(d[0]), "=f"(d[1]), "=f"(d[2]), "=f"(d[3]), "=f"(d[4]), "=f"(d[5]), "=f"(d[6]), "=f"(d[7]), "=f"(d[8]), "=f"(d[9]), "=f"(d[10]), "=f"(d[11]), "=f"(d[12]), "=f"(d[13]), "=f"(d[14]), "=f"(d[15]), "=f"(d[16]), "=f"(d[17]), "=f"(d[18]), "=f"(d[19]), "=f"(d[20]), "=f"(d[21]), "=f"(d[22]), "=f"(d[23]), "=f"(d[24]), "=f"(d[25]), "=f"(d[26]), "=f"(d[27]), "=f"(d[28]), "=f"(d[29]), "=f"(d[30]), "=f"(d[31]), "=f"(d[32]), "=f"(d[33]), "=f"(d[34]), "=f"(d[35]), "=f"(d[36]), "=f"(d[37]), "=f"(d[38]), "=f"(d[39]), "=f"(d[40]), "=f"(d[41]), "=f"(d[42]), "=f"(d[43]), "=f"(d[44]), "=f"(d[45]), "=f"(d[46]), "=f"(d[47]), "=f"(d[48]), "=f"(d[49]), "=f"(d[50]), "=f"(d[51]), "=f"(d[52]), "=f"(d[53]), "=f"(d[54]), "=f"(d[55]), "=f"(d[56]), "=f"(d[57]), "=f"(d[58]), "=f"(d[59]), "=f"(d[60]), "=f"(d[61]), "=f"(d[62]), "=f"(d[63]), "=f"(d[64]), "=f"(d[65]), "=f"(d[66]), "=f"(d[67]), "=f"(d[68]), "=f"(d[69]), "=f"(d[70]), "=f"(d[71]), "=f"(d[72]), "=f"(d[73]), "=f"(d[74]), "=f"(d[75]), "=f"(d[76]), "=f"(d[77]), "=f"(d[78]), "=f"(d[79]), "=f"(d[80]), "=f"(d[81]), "=f"(d[82]), "=f"(d[83]), "=f"(d[84]), "=f"(d[85]), "=f"(d[86]), "=f"(d[87]), "=f"(d[88]), "=f"(d[89]), "=f"(d[90]), "=f"(d[91]), "=f"(d[92]), "=f"(d[93]), "=f"(d[94]), "=f"(d[95])
    : "l"(da), "l"(db));
}
__device__ __forceinline__ void wgmma192_rs(float (&d)[128], uint32_t a0, uint32_t a1, uint32_t a2, uint32_t a3, uint64_t db) {
  asm volatile("wgmma.mma_async.sync.aligned.m64n192k16.f32.bf16.bf16 "
    "{%0, %1, %2, %3, %4, %5, %6, %7, %8, %9, %10, %11, %12, %13, %14, %15, %16, %17, %18, %19, %20, %21, %22, %23, %24, %25, %26, %27, %28, %29, %30, %31, %32, %33, %34, %35, %36, %37, %38, %39, %40, %41, %42, %43, %44, %45, %46, %47, %48, %49, %50, %51, %52, %53, %54, %55, %56, %57, %58, %59, %60, %61, %62, %63, %64, %65, %66, %67, %68, %69, %70, %71, %72, %73, %74, %75, %76, %77, %78, %79, %80, %81, %82, %83, %84, %85, %86, %87, %88, %89, %90, %91, %92, %93, %94, %95}, {%96, %97, %98, %99}, %100, 1, 1, 1, 1;"
    : "+f"(d[0]), "+f"(d[1]), "+f"(d[2]), "+f"(d[3]), "+f"(d[4]), "+f"(d[5]), "+f"(d[6]), "+f"(d[7]), "+f"(d[8]), "+f"(d[9]), "+f"(d[10]), "+f"(d[11]), "+f"(d[12]), "+f"(d[13]), "+f"(d[14]), "+f"(d[15]), "+f"(d[16]), "+f"(d[17]), "+f"(d[18]), "+f"(d[19]), "+f"(d[20]), "+f"(d[21]), "+f"(d[22]), "+f"(d[23]), "+f"(d[24]), "+f"(d[25]), "+f"(d[26]), "+f"(d[27]), "+f"(d[28]), "+f"(d[29]), "+f"(d[30]), "+f"(d[31]), "+f"(d[32]), "+f"(d[33]), "+f"(d[34]), "+f"(d[35]), "+f"(d[36]), "+f"(d[37]), "+f"(d[38]), "+f"(d[39]), "+f"(d[40]), "+f"(d[41]), "+f"(d[42]), "+f"(d[43]), "+f"(d[44]), "+f"(d[45]), "+f"(d[46]), "+f"(d[47]), "+f"(d[48]), "+f"(d[49]), "+f"(d[50]), "+f"(d[51]), "+f"(d[52]), "+f"(d[53]), "+f"(d[54]), "+f"(d[55]), "+f"(d[56]), "+f"(d[57]), "+f"(d[58]), "+f"(d[59]), "+f"(d[60]), "+f"(d[61]), "+f"(d[62]), "+f"(d[63]), "+f"(d[64]), "+f"(d[65]), "+f"(d[66]), "+f"(d[67]), "+f"(d[68]), "+f"(d[69]), "+f"(d[70]), "+f"(d[71]), "+f"(d[72]), "+f"(d[73]), "+f"(d[74]), "+f"(d[75]), "+f"(d[76]), "+f"(d[77]), "+f"(d[78]), "+f"(d[79]), "+f"(d[80]), "+f"(d[81]), "+f"(d[82]), "+f"(d[83]), "+f"(d[84]), "+f"(d[85]), "+f"(d[86]), "+f"(d[87]), "+f"(d[88]), "+f"(d[89]), "+f"(d[90]), "+f"(d[91]), "+f"(d[92]), "+f"(d[93]), "+f"(d[94]), "+f"(d[95])
    : "r"(a0), "r"(a1), "r"(a2), "r"(a3), "l"(db));
}

__device__ __forceinline__ void wgmma256(float (&d)[128], uint64_t da, uint64_t db) {
  asm volatile("wgmma.mma_async.sync.aligned.m64n256k16.f32.bf16.bf16 "
    "{%0, %1, %2, %3, %4, %5, %6, %7, %8, %9, %10, %11, %12, %13, %14, %15, %16, %17, %18, %19, %20, %21, %22, %23, %24, %25, %26, %27, %28, %29, %30, %31, %32, %33, %34, %35, %36, %37, %38, %39, %40, %41, %42, %43, %44, %45, %46, %47, %48, %49, %50, %51, %52, %53, %54, %55, %56, %57, %58, %59, %60, %61, %62, %63, %64, %65, %66, %67, %68, %69, %70, %71, %72, %73, %74, %75, %76, %77, %78, %79, %80, %81, %82, %83, %84, %85, %86, %87, %88, %89, %90, %91, %92, %93, %94, %95, %96, %97, %98, %99, %100, %101, %102, %103, %104, %105, %106, %107, %108, %109, %110, %111, %112, %113, %114, %115, %116, %117, %118, %119, %120, %121, %122, %123, %124, %125, %126, %127}, %128, %129, 1, 1, 1, 0, 1;"
    : "+f"(d[0]), "+f"(d[1]), "+f"(d[2]), "+f"(d[3]), "+f"(d[4]), "+f"(d[5]), "+f"(d[6]), "+f"(d[7]), "+f"(d[8]), "+f"(d[9]), "+f"(d[10]), "+f"(d[11]), "+f"(d[12]), "+f"(d[13]), "+f"(d[14]), "+f"(d[15]), "+f"(d[16]), "+f"(d[17]), "+f"(d[18]), "+f"(d[19]), "+f"(d[20]), "+f"(d[21]), "+f"(d[22]), "+f"(d[23]), "+f"(d[24]), "+f"(d[25]), "+f"(d[26]), "+f"(d[27]), "+f"(d[28]), "+f"(d[29]), "+f"(d[30]), "+f"(d[31]), "+f"(d[32]), "+f"(d[33]), "+f"(d[34]), "+f"(d[35]), "+f"(d[36]), "+f"(d[37]), "+f"(d[38]), "+f"(d[39]), "+f"(d[40]), "+f"(d[41]), "+f"(d[42]), "+f"(d[43]), "+f"(d[44]), "+f"(d[45]), "+f"(d[46]), "+f"(d[47]), "+f"(d[48]), "+f"(d[49]), "+f"(d[50]), "+f"(d[51]), "+f"(d[52]), "+f"(d[53]), "+f"(d[54]), "+f"(d[55]), "+f"(d[56]), "+f"(d[57]), "+f"(d[58]), "+f"(d[59]), "+f"(d[60]), "+f"(d[61]), "+f"(d[62]), "+f"(d[63]), "+f"(d[64]), "+f"(d[65]), "+f"(d[66]), "+f"(d[67]), "+f"(d[68]), "+f"(d[69]), "+f"(d[70]), "+f"(d[71]), "+f"(d[72]), "+f"(d[73]), "+f"(d[74]), "+f"(d[75]), "+f"(d[76]), "+f"(d[77]), "+f"(d[78]), "+f"(d[79]), "+f"(d[80]), "+f"(d[81]), "+f"(d[82]), "+f"(d[83]), "+f"(d[84]), "+f"(d[85]), "+f"(d[86]), "+f"(d[87]), "+f"(d[88]), "+f"(d[89]), "+f"(d[90]), "+f"(d[91]), "+f"(d[92]), "+f"(d[93]), "+f"(d[94]), "+f"(d[95]), "+f"(d[96]), "+f"(d[97]), "+f"(d[98]), "+f"(d[99]), "+f"(d[100]), "+f"(d[101]), "+f"(d[102]), "+f"(d[103]), "+f"(d[104]), "+f"(d[105]), "+f"(d[106]), "+f"(d[107]), "+f"(d[108]), "+f"(d[109]), "+f"(d[110]), "+f"(d[111]), "+f"(d[112]), "+f"(d[113]), "+f"(d[114]), "+f"(d[115]), "+f"(d[116]), "+f"(d[117]), "+f"(d[118]), "+f"(d[119]), "+f"(d[120]), "+f"(d[121]), "+f"(d[122]), "+f"(d[123]), "+f"(d[124]), "+f"(d[125]), "+f"(d[126]), "+f"(d[127])
    : "l"(da), "l"(db));
}
__device__ __forceinline__ void wgmma256_init(float (&d)[128], uint64_t da, uint64_t db) {
  asm volatile("wgmma.mma_async.sync.aligned.m64n256k16.f32.bf16.bf16 "
    "{%0, %1, %2, %3, %4, %5, %6, %7, %8, %9, %10, %11, %12, %13, %14, %15, %16, %17, %18, %19, %20, %21, %22, %23, %24, %25, %26, %27, %28, %29, %30, %31, %32, %33, %34, %35, %36, %37, %38, %39, %40, %41, %42, %43, %44, %45, %46, %47, %48, %49, %50, %51, %52, %53, %54, %55, %56, %57, %58, %59, %60, %61, %62, %63, %64, %65, %66, %67, %68, %69, %70, %71, %72, %73, %74, %75, %76, %77, %78, %79, %80, %81, %82, %83, %84, %85, %86, %87, %88, %89, %90, %91, %92, %93, %94, %95, %96, %97, %98, %99, %100, %101, %102, %103, %104, %105, %106, %107, %108, %109, %110, %111, %112, %113, %114, %115, %116, %117, %118, %119, %120, %121, %122, %123, %124, %125, %126, %127}, %128, %129, 0, 1, 1, 0, 1;"
    : "=f"(d[0]), "=f"(d[1]), "=f"(d[2]), "=f"(d[3]), "=f"(d[4]), "=f"(d[5]), "=f"(d[6]), "=f"(d[7]), "=f"(d[8]), "=f"(d[9]), "=f"(d[10]), "=f"(d[11]), "=f"(d[12]), "=f"(d[13]), "=f"(d[14]), "=f"(d[15]), "=f"(d[16]), "=f"(d[17]), "=f"(d[18]), "=f"(d[19]), "=f"(d[20]), "=f"(d[21]), "=f"(d[22]), "=f"(d[23]), "=f"(d[24]), "=f"(d[25]), "=f"(d[26]), "=f"(d[27]), "=f"(d[28]), "=f"(d[29]), "=f"(d[30]), "=f"(d[31]), "=f"(d[32]), "=f"(d[33]), "=f"(d[34]), "=f"(d[35]), "=f"(d[36]), "=f"(d[37]), "=f"(d[38]), "=f"(d[39]), "=f"(d[40]), "=f"(d[41]), "=f"(d[42]), "=f"(d[43]), "=f"(d[44]), "=f"(d[45]), "=f"(d[46]), "=f"(d[47]), "=f"(d[48]), "=f"(d[49]), "=f"(d[50]), "=f"(d[51]), "=f"(d[52]), "=f"(d[53]), "=f"(d[54]), "=f"(d[55]), "=f"(d[56]), "=f"(d[57]), "=f"(d[58]), "=f"(d[59]), "=f"(d[60]), "=f"(d[61]), "=f"(d[62]), "=f"(d[63]), "=f"(d[64]), "=f"(d[65]), "=f"(d[66]), "=f"(d[67]), "=f"(d[68]), "=f"(d[69]), "=f"(d[70]), "=f"(d[71]), "=f"(d[72]), "=f"(d[73]), "=f"(d[74]), "=f"(d[75]), "=f"(d[76]), "=f"(d[77]), "=f"(d[78]), "=f"(d[79]), "=f"(d[80]), "=f"(d[81]), "=f"(d[82]), "=f"(d[83]), "=f"(d[84]), "=f"(d[85]), "=f"(d[86]), "=f"(d[87]), "=f"(d[88]), "=f"(d[89]), "=f"(d[90]), "=f"(d[91]), "=f"(d[92]), "=f"(d[93]), "=f"(d[94]), "=f"(d[95]), "=f"(d[96]), "=f"(d[97]), "=f"(d[98]), "=f"(d[99]), "=f"(d[100]), "=f"(d[101]), "=f"(d[102]), "=f"(d[103]), "=f"(d[104]), "=f"(d[105]), "=f"(d[106]), "=f"(d[107]), "=f"(d[108]), "=f"(d[109]), "=f"(d[110]), "=f"(d[111]), "=f"(d[112]), "=f"(d[113]), "=f"(d[114]), "=f"(d[115]), "=f"(d[116]), "=f"(d[117]), "=f"(d[118]), "=f"(d[119]), "=f"(d[120]), "=f"(d[121]), "=f"(d[122]), "=f"(d[123]), "=f"(d[124]), "=f"(d[125]), "=f"(d[126]), "=f"(d[127])
    : "l"(da), "l"(db));
}

namespace {

constexpr int S_LEN = 2048, DM = 1024, DF = 3584;
constexpr int MAXT = 16;
constexpr int MAXPAIRS = 66;
constexpr uint32_t TILE_END = 0xFFFFFFFFu;
constexpr int FLAG_SLEEP = 100;
constexpr int X_STEP = 5;
constexpr int DEF_A = 7, DEF_AW = 5, DEF_G = 8, DEF_R = 4;
constexpr int TAIL = 3;

__device__ __forceinline__ int t_type(uint32_t t) { return t & 3; }
__device__ __forceinline__ int t_mp(uint32_t t) { return (t >> 2) & 7; }
__device__ __forceinline__ int t_idx(uint32_t t) { return (t >> 5) & 31; }
__device__ __forceinline__ int t_k0(uint32_t t) { return (t >> 10) & 63; }
__device__ __forceinline__ int t_nk(uint32_t t) { return (t >> 16) & 63; }
__device__ __forceinline__ int t_sh(uint32_t t) { return (t >> 1) & 1; }
__device__ __forceinline__ int t_deps(uint32_t t, int n) { return ((t_k0(t) + n - 1) >> t_sh(t)) - (t_k0(t) >> t_sh(t)) + 1; }
__device__ __forceinline__ int p1_k(int mp, int k) { return (k + ((mp & 2) << 2)) & 15; }

enum { TM_X1, TM_WQKV, TM_ATTN_ST, TM_ATTN_A, TM_H_A, TM_ACT_A, TM_OUT_ST, TM_OUT16, TM_ACT_ST, TM_WO, TM_WG, TM_WU, TM_WD, TM_COUNT };

struct alignas(64) Params {
  CUtensorMap tm[TM_COUNT];
  const __nv_bfloat16* x;
  const __nv_bfloat16* wo;
  __nv_bfloat16* out;
  int ncta;
  uint32_t sched[MAXPAIRS * MAXT];
};

__device__ __align__(128) __nv_bfloat16 g_attn[S_LEN * DM];
__device__ __align__(128) __nv_bfloat16 g_act[S_LEN * DF];
__device__ __align__(64) uint2 g_xst[S_LEN + 8];
__device__ __align__(128) uint32_t g_csp[16 * 8 * 192];
__device__ __align__(128) uint2 g_rm[DM];
__device__ __align__(128) uint2 g_pdot[16 * S_LEN];
__device__ __align__(128) uint2 g_hmean[S_LEN / 2];
__device__ __align__(128) uint32_t g_hrs[S_LEN];
__device__ __align__(128) uint4 g_halo[16 * 16 * 128];
constexpr int FL_LAUNCH = 0, FL_COPY = 32, FL_OUT = 96, FL_COUNT = FL_OUT + 24 * 32;
__device__ __align__(128) uint32_t g_flags[FL_COUNT];

constexpr int NSTAGE = 4;
constexpr uint32_t STAGE_BYTES = 49152, A_BYTES = 16384;
constexpr uint32_t OFF_STG = NSTAGE * STAGE_BYTES;
constexpr uint32_t OFF_BAR = OFF_STG + 32768;
constexpr uint32_t B_FULL = OFF_BAR, B_EMPTY = OFF_BAR + 32, B_OUTF = OFF_BAR + 64, B_OUTE = OFF_BAR + 96, B_ROW = OFF_BAR + 128,
                   B_HALO = OFF_BAR + 176, B_RM = OFF_BAR + 192, B_EPOCH = OFF_BAR + 200, B_CS = OFF_BAR + 208,
                   B_ROWDONE = OFF_BAR + 216, B_GATE = OFF_BAR + 224, B_COPY = OFF_BAR + 232, B_DUMP = OFF_BAR + 168;
constexpr uint32_t B_HALF = OFF_BAR + 240, B_GO = OFF_BAR + 248, B_DUTY = OFF_BAR + 264;
constexpr uint32_t OFF_MISC = OFF_BAR + 272;
constexpr uint32_t M_EPOCH = OFF_MISC, M_DEP = OFF_MISC + 8, M_PAD = OFF_MISC + 16, M_CS = OFF_MISC + 32, M_RM = M_CS + 768 + 96;
constexpr uint32_t SMEM_BYTES = M_RM + 256;

__device__ __forceinline__ void mbar_init(uint32_t bar, uint32_t cnt) { asm volatile("mbarrier.init.shared::cta.b64 [%0], %1;" :: "r"(bar), "r"(cnt)); }
__device__ __forceinline__ void mbar_arrive(uint32_t bar) { asm volatile("mbarrier.arrive.shared::cta.b64 _, [%0];" :: "r"(bar) : "memory"); }
__device__ __forceinline__ void mbar_arrive_warp(uint32_t bar) {
  __syncwarp();
  asm volatile("{\n.reg .pred p;\nelect.sync _|p, 0xffffffff;\n@p mbarrier.arrive.shared::cta.b64 _, [%0];\n}" :: "r"(bar) : "memory");
}
__device__ __forceinline__ uint32_t mapa(uint32_t addr, uint32_t cta) {
  uint32_t r; asm("mapa.shared::cluster.u32 %0, %1, %2;" : "=r"(r) : "r"(addr), "r"(cta)); return r;
}
__device__ __forceinline__ void mbar_arrive_remote(uint32_t cluster_addr) {
  asm volatile("mbarrier.arrive.shared::cluster.b64 _, [%0];" :: "r"(cluster_addr) : "memory");
}
__device__ __forceinline__ void mbar_wait(uint32_t bar, uint32_t parity) {
  asm volatile("{\n.reg .pred p;\nWAIT_LOOP:\n"
               "mbarrier.try_wait.parity.shared::cta.b64 p, [%0], %1, 5000;\n@!p bra WAIT_LOOP;\n}"
               :: "r"(bar), "r"(parity) : "memory");
}
__device__ __forceinline__ bool mbar_test(uint32_t bar, uint32_t parity) {
  uint32_t ok;
  asm volatile("{\n.reg .pred p;\nmbarrier.test_wait.parity.shared::cta.b64 p, [%1], %2;\nselp.u32 %0, 1, 0, p;\n}"
               : "=r"(ok) : "r"(bar), "r"(parity) : "memory");
  return __all_sync(0xffffffffu, ok != 0);
}
__device__ __forceinline__ void flag_add(uint32_t* flag, uint32_t n) {
  asm volatile("{\n.reg .pred p;\nfence.release.gpu;\nsetp.ne.u64 p, %0, 0;\n@p red.relaxed.gpu.global.add.u32 [%0], %1;\n}" :: "l"(flag), "r"(n) : "memory");
}
__device__ __forceinline__ void fence_async_all() { asm volatile("fence.proxy.async.global;" ::: "memory"); }
__device__ __forceinline__ void fence_async_smem() { asm volatile("fence.proxy.async.shared::cta;" ::: "memory"); }

__device__ __forceinline__ void tma_st3d(const CUtensorMap* m, uint32_t src, int c0, int c1, int c2) {
  asm volatile("{\n.reg .pred p;\nelect.sync _|p, 0xffffffff;\n"
               "@p cp.async.bulk.tensor.3d.global.shared::cta.bulk_group [%0, {%2, %3, %4}], [%1];\n}"
               :: "l"(m), "r"(src), "r"(c0), "r"(c1), "r"(c2) : "memory");
}
__device__ __forceinline__ void tma_add3d(const CUtensorMap* m, uint32_t src, int c0, int c1, int c2) {
  asm volatile("{\n.reg .pred p;\nelect.sync _|p, 0xffffffff;\n"
               "@p cp.reduce.async.bulk.tensor.3d.global.shared::cta.add.tile.bulk_group [%0, {%2, %3, %4}], [%1];\n}"
               :: "l"(m), "r"(src), "r"(c0), "r"(c1), "r"(c2) : "memory");
}
__device__ __forceinline__ void bulk_commit() { asm volatile("cp.async.bulk.commit_group;" ::: "memory"); }
template <int N> __device__ __forceinline__ void bulk_wait_read() { asm volatile("cp.async.bulk.wait_group.read %0;" :: "n"(N) : "memory"); }
__device__ __forceinline__ void bulk_wait_all() { asm volatile("cp.async.bulk.wait_group 0;" ::: "memory"); }

__device__ __forceinline__ void wg_fence() { asm volatile("wgmma.fence.sync.aligned;" ::: "memory"); }
__device__ __forceinline__ void wg_commit() { asm volatile("wgmma.commit_group.sync.aligned;" ::: "memory"); }
template <int N> __device__ __forceinline__ void wg_wait() { asm volatile("wgmma.wait_group.sync.aligned %0;" :: "n"(N) : "memory"); }
__device__ __forceinline__ uint64_t desc64(uint32_t lo) { return ((uint64_t)0x40000040u << 32) | lo; }

__device__ __forceinline__ uint32_t pack2(float lo, float hi) { uint32_t r; asm("cvt.rn.bf16x2.f32 %0, %1, %2;" : "=r"(r) : "f"(hi), "f"(lo)); return r; }
__device__ __forceinline__ float bf_lo(uint32_t v) { return __uint_as_float(v << 16); }
__device__ __forceinline__ float bf_hi(uint32_t v) { return __uint_as_float(v & 0xffff0000u); }
__device__ __forceinline__ uint32_t add2(uint32_t a, uint32_t b) { uint32_t r; asm("add.rn.bf16x2 %0, %1, %2;" : "=r"(r) : "r"(a), "r"(b)); return r; }
__device__ __forceinline__ uint32_t fma2(uint32_t a, uint32_t b, uint32_t c) { uint32_t r; asm("fma.rn.bf16x2 %0, %1, %2, %3;" : "=r"(r) : "r"(a), "r"(b), "r"(c)); return r; }
__device__ __forceinline__ uint32_t mul2(uint32_t a, uint32_t b) { uint32_t r; asm("mul.rn.bf16x2 %0, %1, %2;" : "=r"(r) : "r"(a), "r"(b)); return r; }
__device__ __forceinline__ float tanh_hw(float x) { float y; asm("tanh.approx.f32 %0, %1;" : "=f"(y) : "f"(x)); return y; }
__device__ __forceinline__ float ex2(float x) { float y; asm("ex2.approx.ftz.f32 %0, %1;" : "=f"(y) : "f"(x)); return y; }
__device__ __forceinline__ float rcp(float x) { float y; asm("rcp.approx.ftz.f32 %0, %1;" : "=f"(y) : "f"(x)); return y; }
__device__ __forceinline__ void stsm4(uint32_t addr, uint32_t a, uint32_t b, uint32_t c, uint32_t d) {
  asm volatile("stmatrix.sync.aligned.m8n8.x4.shared.b16 [%0], {%1, %2, %3, %4};" :: "r"(addr), "r"(a), "r"(b), "r"(c), "r"(d) : "memory");
}
__device__ __forceinline__ void stsm4t(uint32_t addr, uint32_t a, uint32_t b, uint32_t c, uint32_t d) {
  asm volatile("stmatrix.sync.aligned.m8n8.x4.trans.shared.b16 [%0], {%1, %2, %3, %4};" :: "r"(addr), "r"(a), "r"(b), "r"(c), "r"(d) : "memory");
}
__device__ __forceinline__ uint4 ld_gpu128(const uint4* p) {
  uint4 v;
  asm volatile("ld.relaxed.gpu.global.v4.u32 {%0, %1, %2, %3}, [%4];" : "=r"(v.x), "=r"(v.y), "=r"(v.z), "=r"(v.w) : "l"(p) : "memory");
  return v;
}
template <int OFF>
__device__ __forceinline__ uint2 ld_gpu64(const void* p) {
  uint2 v;
  asm volatile("ld.relaxed.gpu.global.v2.u32 {%0, %1}, [%2 + %3];" : "=r"(v.x), "=r"(v.y) : "l"(p), "n"(OFF) : "memory");
  return v;
}
__device__ __forceinline__ void st_gpu128_if(bool on, uint4* p, uint32_t a, uint32_t b, uint32_t c, uint32_t d) {
  asm volatile("{\n.reg .pred p;\nsetp.ne.u32 p, %5, 0;\n@p st.relaxed.gpu.global.v4.u32 [%0], {%1, %2, %3, %4};\n}"
               :: "l"(p), "r"(a), "r"(b), "r"(c), "r"(d), "r"((uint32_t)on) : "memory");
}
__device__ __forceinline__ void st_gpu64_if(bool on, uint2* p, uint32_t a, uint32_t b) {
  asm volatile("{\n.reg .pred p;\nsetp.ne.u32 p, %3, 0;\n@p st.relaxed.gpu.global.v2.u32 [%0], {%1, %2};\n}"
               :: "l"(p), "r"(a), "r"(b), "r"((uint32_t)on) : "memory");
}
template <int OFF>
__device__ __forceinline__ uint32_t ld_gpu32(const void* p) {
  uint32_t v;
  asm volatile("ld.relaxed.gpu.global.u32 %0, [%1 + %2];" : "=r"(v) : "l"(p), "n"(OFF) : "memory");
  return v;
}
__device__ __forceinline__ void st_gpu32_if(bool on, uint32_t* p, uint32_t a) {
  asm volatile("{\n.reg .pred p;\nsetp.ne.u32 p, %2, 0;\n@p st.relaxed.gpu.global.u32 [%0], %1;\n}" :: "l"(p), "r"(a), "r"((uint32_t)on) : "memory");
}
__device__ __forceinline__ uint32_t tagged(float v, uint32_t tag) { return __byte_perm(__float_as_uint(v), tag, 0x3214); }
__device__ __forceinline__ float untagged(uint32_t v) { return __uint_as_float(v & ~255u); }
__device__ __forceinline__ uint32_t lds32(uint32_t a) {
  uint32_t v;
  asm volatile("ld.shared.u32 %0, [%1];" : "=r"(v) : "r"(a) : "memory");
  return v;
}
__device__ __forceinline__ uint4 lds128(uint32_t a) {
  uint4 v;
  asm volatile("ld.shared.v4.u32 {%0, %1, %2, %3}, [%4];" : "=r"(v.x), "=r"(v.y), "=r"(v.z), "=r"(v.w) : "r"(a) : "memory");
  return v;
}
__device__ __forceinline__ void ldsm4(uint32_t addr, uint32_t& a, uint32_t& b, uint32_t& c, uint32_t& d) {
  asm volatile("ldmatrix.sync.aligned.m8n8.x4.shared.b16 {%0, %1, %2, %3}, [%4];" : "=r"(a), "=r"(b), "=r"(c), "=r"(d) : "r"(addr) : "memory");
}
__device__ __forceinline__ uint32_t movmat(uint32_t a) { uint32_t d; asm volatile("movmatrix.sync.aligned.m8n8.trans.b16 %0, %1;" : "=r"(d) : "r"(a)); return d; }
__device__ __forceinline__ void mma16(float (&d)[4], uint32_t a0, uint32_t a1, uint32_t a2, uint32_t a3, uint32_t b0, uint32_t b1) {
  asm volatile("mma.sync.aligned.m16n8k16.row.col.f32.bf16.bf16.f32 {%0, %1, %2, %3}, {%4, %5, %6, %7}, {%8, %9}, {%0, %1, %2, %3};"
               : "+f"(d[0]), "+f"(d[1]), "+f"(d[2]), "+f"(d[3]) : "r"(a0), "r"(a1), "r"(a2), "r"(a3), "r"(b0), "r"(b1));
}
__device__ __forceinline__ void mma16_init(float (&d)[4], uint32_t a0, uint32_t a1, uint32_t a2, uint32_t a3, uint32_t b0, uint32_t b1) {
  asm volatile("mma.sync.aligned.m16n8k16.row.col.f32.bf16.bf16.f32 {%0, %1, %2, %3}, {%4, %5, %6, %7}, {%8, %9}, {%10, %10, %10, %10};"
               : "=f"(d[0]), "=f"(d[1]), "=f"(d[2]), "=f"(d[3]) : "r"(a0), "r"(a1), "r"(a2), "r"(a3), "r"(b0), "r"(b1), "f"(0.f));
}
__device__ __forceinline__ float quad_sum(float v) { v += __shfl_xor_sync(0xffffffffu, v, 1); return v + __shfl_xor_sync(0xffffffffu, v, 2); }
__device__ __forceinline__ float quad_max(float v) { v = fmaxf(v, __shfl_xor_sync(0xffffffffu, v, 1)); return fmaxf(v, __shfl_xor_sync(0xffffffffu, v, 2)); }

__device__ __forceinline__ int fresh_tid() { int t; asm volatile("mov.u32 %0, %%tid.x;" : "=r"(t)); return t; }

__device__ __forceinline__ void mbar_spin(uint32_t bar, uint32_t parity) {
  asm volatile("{\n.reg .pred p;\nWAIT_LOOP:\nmbarrier.try_wait.parity.shared::cta.b64 p, [%0], %1;\n@!p bra WAIT_LOOP;\n}" :: "r"(bar), "r"(parity) : "memory");
}

struct Cons {
  uint32_t sb;
  uint32_t empty_r;
  uint32_t srow;
  int w, rank;
  uint32_t s, ph;
  uint32_t prev;
  uint32_t phb;
};

__device__ __forceinline__ void release_prev(Cons& c) {
  if (c.prev < NSTAGE && c.empty_r) mbar_arrive_remote(c.empty_r + 8 * c.prev);
}

template <int N, bool FIRST = false, bool WAIT = true>
__device__ __forceinline__ void mma_step(Cons& c, float (&acc)[128]) {
  if (WAIT) mbar_spin(c.sb + B_FULL + 8 * c.s, c.ph);
  const uint32_t st = ((c.sb & 0x3FFFF) >> 4) + c.s * (STAGE_BYTES >> 4);
  const uint32_t da = st + c.w * 512 + (1u << 16);
  const uint32_t db = st + (A_BYTES >> 4) + ((N == 192 ? 256u : 512u) << 16);
  wg_fence();
#pragma unroll
  for (int kk = 0; kk < 4; kk++) {
    const uint32_t bo = N == 192 ? (kk >> 1) * 768 + (kk & 1) * 128 : kk * 128;
    if (FIRST && kk == 0) {
      if (N == 192) wgmma192_init(acc, desc64(da), desc64(db));
      else wgmma256_init(acc, desc64(da), desc64(db));
    } else {
      if (N == 192) wgmma192(acc, desc64(da + kk * 2), desc64(db + bo));
      else wgmma256(acc, desc64(da + kk * 2), desc64(db + bo));
    }
    if (kk == 0) {
      wg_commit();
      wg_wait<1>();
      release_prev(c);
    }
  }
  wg_commit();
  c.prev = c.s;
  if (++c.s == NSTAGE) { c.s = 0; c.ph ^= 1; }
}

template <int CHUNK>
__device__ __forceinline__ uint32_t srow(const Cons& c) {
  if (CHUNK == 0) return c.srow;
  uint32_t r;
  asm volatile("xor.b32 %0, %1, %2;" : "=r"(r) : "r"(c.srow), "n"(CHUNK << 4));
  return r;
}
__device__ __forceinline__ void out_acquire(Cons& c, int sub) {
  mbar_spin(c.sb + B_OUTE + c.w * 16 + sub * 8, ((c.phb >> sub) & 1) ^ 1);
  c.phb ^= 1u << sub;
}
__device__ __forceinline__ void out_publish(const Cons& c, int sub) {
  fence_async_smem();
  mbar_arrive_warp(c.sb + B_OUTF + c.w * 16 + sub * 8);
}

__device__ __forceinline__ float asf(uint32_t v) { return __uint_as_float(v); }
__device__ __forceinline__ uint32_t asu(float v) { return __float_as_uint(v); }

__device__ __forceinline__ void sched_fence(uint32_t sb) {
  asm volatile("{\n.reg .pred p;\n.reg .u32 t;\nmov.u32 t, %%clock;\nsetp.eq.u32 p, t, 0;\n@p st.shared.u32 [%0], t;\n}" :: "r"(sb + M_PAD) : "memory");
}

template <int N, bool FIRST = false, bool WAIT = true>
__device__ __forceinline__ void next_step(Cons& c, float (&acc)[128]) {
  if (N) {
    if (!WAIT) {
      sched_fence(c.sb);
      asm volatile("bar.sync 3, 256;" ::: "memory");
    }
    mma_step<N, FIRST, WAIT>(c, acc);
    sched_fence(c.sb);
  }
}

__device__ __forceinline__ void p1_park(const Cons& c, const float (&acc)[128], uint32_t (&lo)[24], uint32_t (&hi)[24], int g, uint32_t tile) {
#pragma unroll
  for (int j = 8; j < 24; j++) hi[j] = pack2(acc[4 * j + 2], acc[4 * j + 3]);
  const int l = fresh_tid() & 31;
  if (g < 8) {
#pragma unroll
    for (int i = 0; i < 4; i++)
      stsm4(c.sb + OFF_STG + (g >> 2) * 16384 + (g & 3) * 2048 + l * 16 + i * 512, hi[8 + 4 * i], hi[9 + 4 * i], hi[10 + 4 * i], hi[11 + 4 * i]);
    mbar_arrive_warp(c.sb + B_HALO + (g >> 2) * 8);
  } else {
    uint4* box = g_halo + ((t_mp(tile) * 2 + c.rank) * 16 + t_idx(tile)) * 128 + l;
#pragma unroll
    for (int i = 0; i < 4; i++) st_gpu128_if(t_mp(tile) < 7, box + i * 32, ~hi[8 + 4 * i], ~hi[9 + 4 * i], ~hi[10 + 4 * i], ~hi[11 + 4 * i]);
  }
#pragma unroll
  for (int j = 0; j < 8; j++) hi[j] = pack2(acc[4 * j + 2], acc[4 * j + 3]);
#pragma unroll
  for (int j = 0; j < 24; j++) lo[j] = pack2(acc[4 * j], acc[4 * j + 1]);
}

__device__ __forceinline__ void p1_centre(const Cons& c, float (&acc)[128], float mu0, float mu1) {
  const uint32_t on = (fresh_tid() & 3) == 0 ? 0xffffffffu : 0u;
  const uint32_t h0 = pack2(-mu0, -mu0), h1 = pack2(-mu1, -mu1);
  const float r0 = -mu0 - bf_lo(h0), r1 = -mu1 - bf_lo(h1);
  const uint32_t a0 = h0 & on, a1 = h1 & on, a2 = pack2(r0, r0) & on, a3 = pack2(r1, r1) & on;
  wg_fence();
  wgmma192_rs(acc, a0, a1, a2, a3, ((uint64_t)2 << 32) | (((c.sb + M_CS) & 0x3FFFF) >> 4));
  wg_commit();
}

template <int DEFER>
__device__ __forceinline__ void p1_attention(Cons& c, float (&acc)[128], uint32_t (&lo)[24], uint32_t (&hi)[24], const float (&ev)[8], uint32_t tile) {
  next_step<DEFER, true>(c, acc);
  if (DEFER < 256) next_step<DEFER>(c, acc);
  const int tw = fresh_tid() & 127, l = tw & 31, q = l & 3, r = l >> 2;
  const uint32_t mine = c.sb + OFF_STG + c.w * 16384 + (tw >> 5) * 2048 + l * 16;
#pragma unroll
  for (int j = 16; j < 24; j++) { lo[j] = movmat(lo[j]); hi[j] = movmat(hi[j]); }
  const bool c0 = 2 * q <= r, c1 = 2 * q + 1 <= r;
  constexpr float QS = 0.17677669529663687f * 1.4426950408889634f;
  const float kl0 = c0 ? ev[4] : ev[2], kl1 = c1 ? ev[5] : ev[3], ql0 = ev[0] * QS * kl0, ql1 = ev[0] * QS * kl1;
  const float kh0 = c0 ? ev[6] : ev[4], kh1 = c1 ? ev[7] : ev[5], qh0 = ev[1] * QS * kh0, qh1 = ev[1] * QS * kh1;
  next_step<DEFER>(c, acc);
  mbar_spin(c.sb + B_HALO + c.w * 8, (c.phb >> 2) & 1);
  c.phb ^= 4;
  float sp[2][4], s0[2][4], s1[2][4];
  {
    uint32_t kp[8];
    ldsm4(mine, kp[0], kp[1], kp[2], kp[3]);
    ldsm4(mine + 512, kp[4], kp[5], kp[6], kp[7]);
    if (DEFER) { mbar_spin(c.sb + B_FULL + 8 * c.s, c.ph); sched_fence(c.sb); }
#pragma unroll
    for (int h = 0; h < 2; h++) {
      const int a = 4 * h, b = a + 2;
      mma16_init(s0[h], lo[a], hi[a], lo[a + 1], hi[a + 1], lo[8 + a], lo[9 + a]);
      mma16_init(s1[h], lo[a], hi[a], lo[a + 1], hi[a + 1], hi[8 + a], hi[9 + a]);
      mma16_init(sp[h], lo[a], hi[a], lo[a + 1], hi[a + 1], kp[a], kp[a + 1]);
      mma16(s0[h], lo[b], hi[b], lo[b + 1], hi[b + 1], lo[8 + b], lo[9 + b]);
      mma16(s1[h], lo[b], hi[b], lo[b + 1], hi[b + 1], hi[8 + b], hi[9 + b]);
      mma16(sp[h], lo[b], hi[b], lo[b + 1], hi[b + 1], kp[b], kp[b + 1]);
    }
  }
  next_step<DEFER, false, false>(c, acc);
  float x[4][2];
  {
    const bool first = (t_mp(tile) | c.w | (tw >> 5)) == 0;
#pragma unroll
    for (int h = 0; h < 2; h++) {
      x[h][0] = first && !c0 ? -INFINITY : (c0 ? s0[h][0] : sp[h][0]) * ql0;
      x[h][1] = first && !c1 ? -INFINITY : (c1 ? s0[h][1] : sp[h][1]) * ql1;
      x[2 + h][0] = (c0 ? s1[h][2] : s0[h][2]) * qh0;
      x[2 + h][1] = (c1 ? s1[h][3] : s0[h][3]) * qh1;
    }
#pragma unroll
    for (int i = 0; i < 4; i++) {
      const float m = quad_max(fmaxf(x[i][0], x[i][1]));
      x[i][0] = ex2(x[i][0] - m); x[i][1] = ex2(x[i][1] - m);
    }
  }
  if (DEFER < 256) next_step<DEFER>(c, acc);
  float ol[4][4], oh[4][4];
  {
    uint32_t vp[4][4], pb[4][2];
#pragma unroll
    for (int m = 0; m < 4; m++) {
      asm volatile("ldmatrix.sync.aligned.m8n8.x2.trans.shared.b16 {%0, %1}, [%2];" : "=r"(vp[m][0]), "=r"(vp[m][1]) : "r"(mine + 1024 + m * 256) : "memory");
      asm volatile("xor.b32 %0, %2, %4;\nxor.b32 %1, %3, %4;" : "=r"(vp[m][2]), "=r"(vp[m][3]) : "r"(lo[16 + 2 * m]), "r"(lo[17 + 2 * m]), "r"(c.sb & 1));
    }
    const uint32_t cur = (c0 ? 0x0000ffffu : 0u) | (c1 ? 0xffff0000u : 0u);
#pragma unroll
    for (int i = 0; i < 4; i++) {
      const float inv = rcp(quad_sum(x[i][0] + x[i][1]));
      const uint32_t pr = pack2(x[i][0] * inv * (i < 2 ? kl0 : kh0), x[i][1] * inv * (i < 2 ? kl1 : kh1));
      pb[i][0] = pr & ~cur; pb[i][1] = pr & cur;
    }
    if (DEFER) { mbar_spin(c.sb + B_FULL + 8 * c.s, c.ph); sched_fence(c.sb); }
#pragma unroll
    for (int m = 0; m < 4; m++) {
      mma16_init(oh[m], lo[16 + 2 * m], lo[17 + 2 * m], hi[16 + 2 * m], hi[17 + 2 * m], pb[2 + (m >> 1)][0], pb[2 + (m >> 1)][1]);
      mma16_init(ol[m], vp[m][0], vp[m][1], vp[m][2], vp[m][3], pb[m >> 1][0], pb[m >> 1][1]);
    }
  }
  next_step<DEFER, false, false>(c, acc);
#pragma unroll
  for (int m = 0; m < 4; m++)
    stsm4t(c.srow ^ (m << 5), pack2(ol[m][0], ol[m][1]), pack2(oh[m][0], oh[m][1]), pack2(ol[m][2], ol[m][3]), pack2(oh[m][2], oh[m][3]));
  next_step<DEFER>(c, acc);
  out_publish(c, 0);
  mbar_spin(c.sb + B_RM, 0);
  float d[4] = {0.f, 0.f, 0.f, 0.f};
#pragma unroll
  for (int m = 0; m < 4; m += 2) {
    const uint4 rm = lds128(c.sb + M_RM + m * 64 + r * 16);
    d[0] = fmaf(ol[m][0], asf(rm.x), fmaf(ol[m][2], asf(rm.y), fmaf(ol[m + 1][0], asf(rm.z), fmaf(ol[m + 1][2], asf(rm.w), d[0]))));
    d[1] = fmaf(ol[m][1], asf(rm.x), fmaf(ol[m][3], asf(rm.y), fmaf(ol[m + 1][1], asf(rm.z), fmaf(ol[m + 1][3], asf(rm.w), d[1]))));
    d[2] = fmaf(oh[m][0], asf(rm.x), fmaf(oh[m][2], asf(rm.y), fmaf(oh[m + 1][0], asf(rm.z), fmaf(oh[m + 1][2], asf(rm.w), d[2]))));
    d[3] = fmaf(oh[m][1], asf(rm.x), fmaf(oh[m][3], asf(rm.y), fmaf(oh[m + 1][1], asf(rm.z), fmaf(oh[m + 1][3], asf(rm.w), d[3]))));
  }
  const bool up = l & 16, odd = l & 8;
  const float e0 = (up ? d[2] : d[0]) + __shfl_xor_sync(0xffffffffu, up ? d[0] : d[2], 16);
  const float e1 = (up ? d[3] : d[1]) + __shfl_xor_sync(0xffffffffu, up ? d[1] : d[3], 16);
  float f = (odd ? e1 : e0) + __shfl_xor_sync(0xffffffffu, odd ? e0 : e1, 8);
  f += __shfl_xor_sync(0xffffffffu, f, 4);
  st_gpu64_if(!(l & 4),
              g_pdot + t_idx(tile) * S_LEN + c.rank * 1024 + t_mp(tile) * 128 + c.w * 64 + (tw >> 5) * 16 + (l >> 4) * 8 + 2 * q + ((l >> 3) & 1),
              asu(f), lds32(c.sb + M_EPOCH));
}

__device__ __forceinline__ void cs_accumulate(const Cons& c, uint32_t (&pk)[64], uint32_t off) {
#pragma unroll
  for (int g = 0; g < 3; g++) {
    uint32_t a, b;
    asm volatile("ld.shared.v2.b32 {%0, %1}, [%2];" : "=r"(a), "=r"(b) : "r"(off + c.prev * STAGE_BYTES + g * 4096) : "memory");
    pk[4 * g] = asu(asf(pk[4 * g]) + bf_lo(a)); pk[4 * g + 1] = asu(asf(pk[4 * g + 1]) + bf_hi(a));
    pk[4 * g + 2] = asu(asf(pk[4 * g + 2]) + bf_lo(b)); pk[4 * g + 3] = asu(asf(pk[4 * g + 3]) + bf_hi(b));
  }
}
__device__ __forceinline__ void cs_dump(const Cons& c, const uint32_t (&pk)[64]) {
  const int t = fresh_tid();
  const bool up = t & 16;
#pragma unroll
  for (int g = 0; g < 3; g++) {
    const float a = asf(up ? pk[4 * g + 2] : pk[4 * g]) + __shfl_xor_sync(0xffffffffu, asf(up ? pk[4 * g] : pk[4 * g + 2]), 16);
    const float b = asf(up ? pk[4 * g + 3] : pk[4 * g + 1]) + __shfl_xor_sync(0xffffffffu, asf(up ? pk[4 * g + 1] : pk[4 * g + 3]), 16);
    asm volatile("st.shared.v2.f32 [%0], {%1, %2};"
                 :: "r"(c.sb + OFF_STG + 16384 + (t >> 5) * 768 + g * 256 + (t & 15) * 16 + (t & 16) / 2), "f"(a), "f"(b) : "memory");
  }
  mbar_arrive_warp(c.sb + B_DUMP);
  mbar_spin(c.sb + B_EPOCH, 0);
}
__device__ __forceinline__ void cs_publish(const Cons& c, uint32_t tile) {
  const int t = min(fresh_tid(), 191);
  mbar_spin(c.sb + B_DUMP, 0);
  float v[8];
#pragma unroll
  for (int g = 0; g < 8; g++) v[g] = asf(lds32(c.sb + OFF_STG + 16384 + g * 768 + t * 4));
  st_gpu32_if(t_mp(tile) < 4, g_csp + (t_idx(tile) * 8 + (t_mp(tile) & 3) * 2 + c.rank) * 192 + t,
              tagged(((v[0] + v[1]) + (v[2] + v[3])) + ((v[4] + v[5]) + (v[6] + v[7])), lds32(c.sb + M_EPOCH)));
}

__device__ __forceinline__ void cs_fetch(uint32_t (&cs)[8], uint32_t tile) {
  const uint32_t* part = g_csp + t_idx(tile) * (8 * 192) + min(fresh_tid(), 191);
#pragma unroll
  for (int i = 0; i < 8; i++) cs[i] = ld_gpu32<0>(part + i * 192);
}
__device__ __forceinline__ void cs_finish(const Cons& c, uint32_t (&cs)[8], uint32_t tile, uint32_t tag) {
  while (true) {
    uint32_t bad = 0;
#pragma unroll
    for (int i = 0; i < 8; i++) bad |= cs[i] ^ tag;
    if (!__any_sync(0xffffffffu, (bad & 255) != 0)) break;
    cs_fetch(cs, tile);
  }
  const float sum = ((untagged(cs[0]) + untagged(cs[1])) + (untagged(cs[2]) + untagged(cs[3]))) + ((untagged(cs[4]) + untagged(cs[5])) + (untagged(cs[6]) + untagged(cs[7])));
  const uint32_t h = pack2(sum, sum), col = min(fresh_tid(), 191);
  asm volatile("st.shared.u16 [%0], %1;\nst.shared.u16 [%0 + 16], %2;"
               :: "r"(c.sb + M_CS + (col >> 3) * 32 + (col & 7) * 2), "h"((uint16_t)h), "h"((uint16_t)pack2(sum - bf_lo(h), 0.f)) : "memory");
  fence_async_smem();
}

template <int C>
__device__ __forceinline__ void g_chunk(Cons& c, uint32_t (&pk)[64], float (&ev)[8]) {
  constexpr float C0 = 0.7978845608028654f, C1 = 0.044715f * 0.7978845608028654f;
  if ((C & 3) == 0) out_acquire(c, C >> 2);
  uint32_t o[4];
#pragma unroll
  for (int i = 0; i < 4; i++) {
    const float rs = ev[i & 1];
    const float k0 = C0 * rs, k1 = C1 * rs * rs * rs, k2 = 0.5f * rs * rs;
    const float g0 = bf_lo(pk[4 * C + i]), g1 = bf_hi(pk[4 * C + i]);
    const float t0 = tanh_hw(g0 * fmaf(g0 * g0, k1, k0)), t1 = tanh_hw(g1 * fmaf(g1 * g1, k1, k0));
    o[i] = mul2(pack2(g0 * fmaf(t0, k2, k2), g1 * fmaf(t1, k2, k2)), pk[32 + 4 * C + i]);
  }
  stsm4(srow<(C & 3) * 2>(c) + (C >> 2) * 8192, o[0], o[1], o[2], o[3]);
  if ((C & 3) == 3) out_publish(c, C >> 2);
}

template <int C>
__device__ __forceinline__ void r_chunk(Cons& c, const uint32_t (&pk)[64], const float (&ev)[8]) {
  uint32_t o[16];
#pragma unroll
  for (int i = 0; i < 16; i++) o[i] = add2(pk[16 * C + i], asu(ev[i & 1]));
  out_acquire(c, C & 1);
  stsm4(srow<0>(c) + (C & 1) * 8192, o[0], o[1], o[2], o[3]);
  stsm4(srow<2>(c) + (C & 1) * 8192, o[4], o[5], o[6], o[7]);
  stsm4(srow<4>(c) + (C & 1) * 8192, o[8], o[9], o[10], o[11]);
  stsm4(srow<6>(c) + (C & 1) * 8192, o[12], o[13], o[14], o[15]);
  out_publish(c, C & 1);
}
template <int H>
__device__ __forceinline__ void mma_half(const Cons& c, float (&acc)[64], int i0, int i1) {
#pragma unroll 1
  for (int i = i0; i < i1; i++) {
    const uint32_t s = (c.s + i) & 3;
    if (H == 0) mbar_spin(c.sb + B_FULL + 8 * s, c.ph ^ ((c.s + i) >> 2));
    wg_fence();
    const uint32_t st = ((c.sb & 0x3FFFF) >> 4) + s * (STAGE_BYTES >> 4);
    const uint32_t da = st + c.w * 512 + (1u << 16), db = st + (A_BYTES >> 4) + H * 1024 + (512u << 16);
#pragma unroll
    for (int kk = 0; kk < 4; kk++) wgmma128(acc, desc64(da + kk * 2), desc64(db + kk * 128));
    wg_commit();
  }
}
__device__ __forceinline__ void release_tail(Cons& c, bool hold) {
#pragma unroll 1
  for (int i = 0; i < TAIL; i++) {
    c.prev = hold ? NSTAGE : c.s;
    release_prev(c);
    if (++c.s == NSTAGE) { c.s = 0; c.ph ^= 1; }
  }
  c.prev = NSTAGE;
}
template <int C, bool ADD>
__device__ __forceinline__ void half_out(const Params& p, const Cons& c, const float (&acc)[64], const float (&ev)[8], bool own,
                                         uint32_t mine, int col, int row) {
#pragma unroll
  for (int i = 4 * C; i < 4 * C + 4; i++) {
    uint32_t o[4];
#pragma unroll
    for (int j = 0; j < 4; j++) {
      o[j] = pack2(acc[8 * i + 2 * j], acc[8 * i + 2 * j + 1]);
      if (ADD) o[j] = add2(o[j], asu(ev[j & 1]));
    }
    stsm4((c.srow ^ ((i & 3) << 5)) + C * 8192, o[0], o[1], o[2], o[3]);
  }
  fence_async_smem();
  __syncwarp();
  if (own) tma_add3d(&p.tm[TM_OUT16], mine + C * 8192, col + C * 64, row, 0);
  else mbar_arrive_warp(c.sb + B_OUTF + c.w * 16 + C * 8);
  sched_fence(c.sb);
}

template <int N>
__device__ __forceinline__ void mma_run(Cons& c, float (&acc)[128], int k0, int k1) {
#pragma unroll 1
  for (int k = k0; k < k1; k++) mma_step<N>(c, acc);
}

__device__ __forceinline__ void tile_end(Cons& c) {
  wg_wait<0>();
  release_prev(c);
  c.prev = NSTAGE;
}

__device__ __forceinline__ void stagger_wait(Cons& c) {
  if (c.w == 1) {
    wg_wait<0>();
    release_prev(c);
    c.prev = NSTAGE;
    asm volatile("bar.sync 7, 256;" ::: "memory");
  }
}

struct RowMeans {
  const uint4* src;
  uint4 v[4], x;
};
__device__ __forceinline__ int first_row(const Cons& c, uint32_t tile) {
  const int t = fresh_tid();
  return (t_mp(tile) * 2 + c.rank) * 128 + (t >> 5) * 16 + ((t & 31) >> 2);
}
__device__ __forceinline__ int mean_slot(const Cons& c, uint32_t tile) {
  const int t = fresh_tid();
  return (t & 4) * 128 + (t_mp(tile) * 2 + c.rank) * 32 + (t >> 5) * 4 + (t & 3);
}
__device__ __forceinline__ void row_means_fetch(RowMeans& s) {
#pragma unroll
  for (int i = 0; i < 4; i++) s.v[i] = ld_gpu128(s.src + i * (2 * S_LEN));
}
__device__ __forceinline__ void row_means_load(RowMeans& s, const Cons& c, uint32_t tile) {
  s.src = nullptr;
  s.v[0] = s.v[1] = s.v[2] = s.v[3] = s.x = make_uint4(0, 0, 0, 0);
  if ((tile >> 22) & 1) {
    const int o = mean_slot(c, tile);
    if (t_type(tile) == 1) {
      s.x = ld_gpu128((const uint4*)(g_xst + 8) + o);
      s.src = (const uint4*)g_pdot + ((fresh_tid() >> 3) & 3) * (S_LEN / 2) + o;
      row_means_fetch(s);
    } else {
      asm volatile("ld.relaxed.gpu.global.u32 %0, [%1];" : "=r"(s.x.x) : "l"(g_hmean + o) : "memory");
    }
  }
}
__device__ __forceinline__ void row_means_finish(RowMeans& s, const Cons& c, uint32_t tile, float (&ev)[8]) {
  ev[0] = ev[1] = 0.f;
  if ((tile >> 22) & 1) {
    uint32_t m = s.x.x;
    if (t_type(tile) == 1) {
      const uint32_t tag = lds32(c.sb + M_EPOCH);
      while (true) {
        uint32_t bad = 0;
#pragma unroll
        for (int i = 0; i < 4; i++) bad |= (s.v[i].y ^ tag) | (s.v[i].w ^ tag);
        if (!__any_sync(0xffffffffu, bad != 0)) break;
        row_means_fetch(s);
      }
      float a = (asf(s.v[0].x) + asf(s.v[1].x)) + (asf(s.v[2].x) + asf(s.v[3].x));
      float b = (asf(s.v[0].z) + asf(s.v[1].z)) + (asf(s.v[2].z) + asf(s.v[3].z));
      a += __shfl_xor_sync(0xffffffffu, a, 8); b += __shfl_xor_sync(0xffffffffu, b, 8);
      a += __shfl_xor_sync(0xffffffffu, a, 16); b += __shfl_xor_sync(0xffffffffu, b, 16);
      m = pack2(a + asf(s.x.x), b + asf(s.x.z));
      st_gpu64_if(t_idx(tile) == 0 && (fresh_tid() & 24) == 0, g_hmean + mean_slot(c, tile), m, tag);
      m ^= 0x80008000u;
    }
    const int r = (fresh_tid() & 31) >> 2, from = (r & 1) * 4 + (r >> 2), sel = r & 2 ? 0x3232 : 0x1010;
    ev[0] = asf(__byte_perm(__shfl_sync(0xffffffffu, m, from), 0, sel));
    ev[1] = asf(__byte_perm(__shfl_sync(0xffffffffu, m, from + 2), 0, sel));
  }
}

__device__ __forceinline__ void consumer(const Params& p, uint32_t sb, int w, int rank, int pair) {
  Cons c;
  c.sb = sb; c.w = w; c.rank = rank;
  const int t0 = threadIdx.x & 127;
  c.empty_r = __shfl_sync(0xffffffffu, t0 < 2 ? mapa(sb + B_EMPTY, t0 & 1) : 0u, t0 & 31);
  c.srow = __shfl_sync(0xffffffffu, sb + OFF_STG + w * 16384 + ((t0 >> 5) * 16 + (t0 & 15)) * 128 + ((((t0 >> 4) & 1) ^ (t0 & 7)) << 4), t0 & 31);
  c.s = 0; c.ph = 0; c.prev = NSTAGE; c.phb = 0;
  float acc[128];
  uint32_t pk[64];
  float ev[8];
  const uint32_t* sched = p.sched + pair * MAXT;
  int ti = 0;
  uint32_t tile = __shfl_sync(0xffffffffu, sched[0], 0);
  const int g = __shfl_sync(0xffffffffu, (threadIdx.x >> 5) + 1, 0);
  int k;
  uint32_t cs[8];

  mma_step<192, true>(c, acc);
  {
    const int t = fresh_tid(), row = (t_mp(tile) & 1) * 16 + (t >> 4);
    const uint32_t off = sb + A_BYTES + rank * 12288 + row * 128 + ((((t >> 1) ^ row) & 7) << 4) + (t & 1) * 8;
#pragma unroll
    for (int i = 0; i < 12; i++) pk[i] = 0;
#pragma unroll 1
    for (k = 1; k < 12; k++) {
      if ((unsigned)(k - X_STEP) < 2u) mbar_arrive_warp(sb + B_GO + 8 * (k - X_STEP));
      if (k < 9) cs_accumulate(c, pk, off);
      if (k == 9) cs_dump(c, pk);
      if (k == 10) cs_publish(c, tile);
      mma_step<192>(c, acc);
    }
    cs_fetch(cs, tile);
  }
started192:
  {
    const uint32_t next = __shfl_sync(0xffffffffu, sched[ti + 1], 0);
    mma_run<192>(c, acc, k, 13);
    const int t = fresh_tid(), q = t & 3, r = (t & 31) >> 2;
    const uint32_t tag = lds32(sb + M_EPOCH);
    const int base = rank * 1024 + t_mp(tile) * 128 + (t >> 5) * 16;
    const uint2* own = g_xst + base + r;
    const uint4* before = (const uint4*)(g_xst + base) + q + (base & 1023 ? 0 : 4);
    uint2 e0 = ld_gpu64<64>(own), e1 = ld_gpu64<128>(own);
    uint4 kp = ld_gpu128(before);
    mbar_spin(sb + B_OUTE + (g >> 2 ? 16 : 0), (c.phb & 1) ^ 1);
    c.phb ^= 1;
#pragma unroll 1
    for (int i = t_nk(tile) - 13; i > 0; i--) {
      if (i == 2) {
        if (ti == 0) cs_finish(c, cs, tile, tag);
        mbar_arrive_warp(sb + B_CS);
      }
      if (i == 1) stagger_wait(c);
      mma_step<192>(c, acc);
    }
    while (true) {
      if (!__any_sync(0xffffffffu, (((e0.y ^ tag) | (e1.y ^ tag) | (kp.y ^ tag) | (kp.w ^ tag)) & 255) != 0)) break;
      e0 = ld_gpu64<64>(own); e1 = ld_gpu64<128>(own);
      kp = ld_gpu128(before);
    }
    mbar_spin(sb + B_CS, (c.phb >> 2) & 1);
    p1_centre(c, acc, asf(e0.x), asf(e1.x));
    if (w == 0) asm volatile("bar.arrive 7, 256;" ::: "memory");
    e0.y &= ~255u; e1.y &= ~255u;
    ev[0] = asf(e0.y); ev[1] = asf(e1.y);
    ev[2] = asf(kp.y & ~255u); ev[3] = asf(kp.w & ~255u);
    ev[4] = asf(__shfl_sync(0xffffffffu, e0.y, 8 * q)); ev[5] = asf(__shfl_sync(0xffffffffu, e0.y, 8 * q + 4));
    ev[6] = asf(__shfl_sync(0xffffffffu, e1.y, 8 * q)); ev[7] = asf(__shfl_sync(0xffffffffu, e1.y, 8 * q + 4));
    const bool defer = !((tile >> 24) & 1);
    tile_end(c);
    ti++;
    uint32_t lo[24], hi[24];
    p1_park(c, acc, lo, hi, g, tile);
    if (defer) {
      k = DEF_A;
      if (t_type(next)) {
        p1_attention<256>(c, acc, lo, hi, ev, tile);
        tile = next;
        k = DEF_AW;
        goto started;
      }
      p1_attention<192>(c, acc, lo, hi, ev, tile);
      tile = next;
      goto again192;
    }
    p1_attention<0>(c, acc, lo, hi, ev, tile);
    tile = next;
  }
fresh:
  if (tile == TILE_END) goto done;
  k = 1;
  if (t_type(tile) == 0) {
    mma_step<192, true>(c, acc);
  again192:
#pragma unroll
    for (int i = 0; i < 8; i++) cs[i] = 0;
    goto started192;
  }
  mma_step<256, true>(c, acc);
started:
  {
    const uint32_t next = __shfl_sync(0xffffffffu, sched[ti + 1], 0);
    mma_run<256>(c, acc, k, t_nk(tile) - TAIL);
    RowMeans means;
    row_means_load(means, c, tile);
    if (next == TILE_END) c.empty_r = 0;
    const bool geglu = t_type(tile) == 2;
    if (!geglu && ((tile >> 24) & 1)) {
      const bool last = next == TILE_END;
      mbar_spin(sb + (last ? B_GATE : B_COPY), 0);
      out_acquire(c, 0);
      out_acquire(c, 1);
      float left[64], right[64];
      wg_wait<0>();
      release_prev(c);
      c.prev = NSTAGE;
#pragma unroll
      for (int i = 0; i < 64; i++) asm volatile("add.f32 %0, %1, 0f80000000;" : "=f"(left[i]) : "f"(acc[i]));
      if (w == 1) asm volatile("bar.sync 7, 256;" ::: "memory");
      mma_half<0>(c, left, 0, TAIL);
      asm volatile("bar.arrive %0, 256;" :: "r"(7 - w) : "memory");
      row_means_finish(means, c, tile, ev);
      const float m0 = bf_lo(asu(ev[0])), m1 = bf_lo(asu(ev[1]));
#pragma unroll
      for (int i = 0; i < 64; i++) asm volatile("add.f32 %0, %1, %2;" : "=f"(right[i]) : "f"(acc[64 + i]), "f"(i & 2 ? m1 : m0));
      const int col = t_idx(tile) * 256, row = (t_mp(tile) * 2 + rank) * 128 + (g - 1) * 16;
      const uint32_t mine = sb + OFF_STG + w * 8192 + (g - 1) * 2048;
      wg_wait<0>();
      half_out<0, true>(p, c, left, ev, true, mine, col, row);
      asm volatile("bar.sync %0, 256;" :: "r"(6 - w) : "memory");
      mma_half<1>(c, right, 0, 1);
      sched_fence(sb);
      half_out<1, true>(p, c, left, ev, true, mine, col, row);
      bulk_commit();
      mma_half<1>(c, right, 1, TAIL);
      if (w == 0) asm volatile("bar.arrive 5, 256;" ::: "memory");
      bulk_wait_all();
      mbar_arrive_warp(sb + B_HALF);
      tile_end(c);
      release_tail(c, (tile >> 25) & w);
      const bool own = last || w == 0;
      half_out<0, false>(p, c, right, ev, own, mine, col + 128, row);
      half_out<1, false>(p, c, right, ev, own, mine, col + 128, row);
      if (own) {
        bulk_commit();
        bulk_wait_all();
        if (last) goto done;
        mbar_arrive_warp(sb + B_OUTF);
        mbar_arrive_warp(sb + B_OUTF + 8);
      }
      ti++;
      tile = next;
      goto fresh;
    }
    uint32_t r0 = 0, r1 = 0;
    if (geglu && !((tile >> 30) & 1)) {
      const uint32_t* hrs = g_hrs + first_row(c, tile);
      r0 = ld_gpu32<0>(hrs); r1 = ld_gpu32<32>(hrs);
    }
#pragma unroll 1
    for (int i = TAIL; i > 0; i--) {
      if (i == 2) stagger_wait(c);
      mma_step<256>(c, acc);
    }
    if (w == 0) asm volatile("bar.arrive 7, 256;" ::: "memory");
    if (!geglu) row_means_finish(means, c, tile, ev);
    const bool defer = !((tile >> 24) & 1);
    const uint32_t parked = tile;
    tile_end(c);
    ti++;
#pragma unroll
    for (int i = 0; i < 64; i++) pk[i] = pack2(acc[2 * i], acc[2 * i + 1]);
    tile = next;
    if (defer) { mma_step<256, true>(c, acc); sched_fence(sb); }
    if (!geglu) {
      r_chunk<0>(c, pk, ev);
#define F(C) mma_step<256>(c, acc); sched_fence(sb); r_chunk<C>(c, pk, ev);
      F(1) F(2) F(3)
#undef F
      k = DEF_R;
      goto started;
    }
    k = DEF_G;
    if ((parked >> 30) & 1) {
      const uint32_t* hrs = g_hrs + first_row(c, parked);
      r0 = ld_gpu32<0>(hrs); r1 = ld_gpu32<32>(hrs);
      if (defer) { mma_step<256>(c, acc); sched_fence(sb); k++; }
    }
    {
      const uint32_t tag = lds32(sb + M_EPOCH);
      while (true) {
        if (!__any_sync(0xffffffffu, (((r0 ^ tag) | (r1 ^ tag)) & 255) != 0)) break;
        const uint32_t* hrs = g_hrs + first_row(c, parked);
        r0 = ld_gpu32<0>(hrs); r1 = ld_gpu32<32>(hrs);
      }
      ev[0] = untagged(r0); ev[1] = untagged(r1);
    }
    g_chunk<0>(c, pk, ev);
#define F(C) if (defer) { mma_step<256>(c, acc); sched_fence(sb); } g_chunk<C>(c, pk, ev);
    F(1) F(2) F(3) F(4) F(5) F(6) F(7)
#undef F
    if (defer) goto started;
    wg_wait<0>();
    goto fresh;
  }
done:;
}

__device__ __forceinline__ uint32_t get_epoch(uint32_t sb) {
  mbar_wait(sb + B_EPOCH, 0);
  return lds32(sb + M_EPOCH);
}
__device__ __forceinline__ bool flag_set(bool seen, const uint32_t* flag, uint32_t target) {
  uint32_t v = target;
  asm volatile("{\n.reg .pred p;\nsetp.eq.u32 p, %2, 0;\n@p ld.acquire.gpu.global.u32 %0, [%1];\n}" : "+r"(v) : "l"(flag), "r"((uint32_t)seen) : "memory");
  return (int32_t)(v - target) >= 0;
}

__device__ __forceinline__ void watcher(const Params& p, uint32_t sb, int pair) {
  const uint32_t* sched = p.sched + pair * MAXT;
  const int l = threadIdx.x & 31;
  const uint32_t target = get_epoch(sb) * 32;
  uint32_t base = 0;
  for (int ti = 1;; ti++) {
    const uint32_t tile = __shfl_sync(0xffffffffu, sched[ti], 0);
    if (tile == TILE_END) break;
    const int ty = t_type(tile);
    if (ty == 0) continue;
    const int n = t_deps(tile, t_nk(tile));
    const uint32_t* flag = g_flags + FL_OUT + ((ty - 1) * 8 + t_mp(tile)) * 32 + (t_k0(tile) >> t_sh(tile)) + l;
    bool ok = l >= n;
    int seen = 0;
    while (true) {
      ok = flag_set(ok, flag, target);
      const int lead = __ffs(~__ballot_sync(0xffffffffu, ok) | 0x80000000u) - 1, now = min(lead, n);
      if (now > seen) {
        asm volatile("{\n.reg .pred p;\nsetp.ne.u32 p, %2, 0;\n@p red.relaxed.cluster.shared::cluster.max.u32 [%0], %1;\n}"
                     :: "r"(mapa(sb + M_DEP, (blockIdx.x ^ l) & 1)), "r"(base + now), "r"((uint32_t)(l < (ty == 3 ? 1 : 2))) : "memory");
        seen = now;
        if (now == n) break;
      } else {
        __nanosleep(FLAG_SLEEP);
      }
    }
    base += n;
  }
}

__device__ __forceinline__ void load_stage(uint32_t bar, uint32_t bytes, uint32_t b, const CUtensorMap* tb, int b0, int b1, int b2,
                                           uint32_t a, const CUtensorMap* ta, int a0, int a1, int a2) {
  asm volatile("{\n.reg .pred p;\nelect.sync _|p, 0xffffffff;\n@p mbarrier.arrive.expect_tx.shared::cta.b64 _, [%0], %1;\n"
               "@p cp.async.bulk.tensor.3d.shared::cluster.global.mbarrier::complete_tx::bytes.multicast::cluster [%2], [%3, {%4, %5, %6}], [%0], %12;\n"
               "@p cp.async.bulk.tensor.3d.shared::cluster.global.mbarrier::complete_tx::bytes [%7], [%8, {%9, %10, %11}], [%0];\n}"
               :: "r"(bar), "r"(bytes), "r"(b), "l"(tb), "r"(b0), "r"(b1), "r"(b2), "r"(a), "l"(ta), "r"(a0), "r"(a1), "r"(a2), "h"((uint16_t)3)
               : "memory");
}

__device__ __forceinline__ void mbar_arrive_if(uint32_t bar) {
  asm volatile("{\n.reg .pred p, q;\nelect.sync _|p, 0xffffffff;\nsetp.ne.and.u32 q, %0, 0, p;\n@q mbarrier.arrive.shared::cta.b64 _, [%0];\n}" :: "r"(bar) : "memory");
}

__device__ __forceinline__ void producer(const Params& p, uint32_t sb, int rank, int pair) {
  const uint32_t* sched = p.sched + pair * MAXT;
  uint32_t n = 1, base = 0;
  mbar_arrive_warp(sb + B_EMPTY);
  for (int ti = 0;; ti++) {
    const uint32_t tile = __shfl_sync(0xffffffffu, sched[ti], 0);
    if (tile == TILE_END) break;
    const int ty = t_type(tile), mp = t_mp(tile), idx = t_idx(tile), nk = t_nk(tile), sh = t_sh(tile);
    const int k0 = ty ? t_k0(tile) : p1_k(mp, 0), kmask = ty ? 63 : 15;
    const CUtensorMap* ta = &p.tm[ty == 0 ? TM_X1 : TM_ATTN_A - 1 + ty];
    const CUtensorMap* tb = &p.tm[ty == 0 ? TM_WQKV : ty == 1 ? TM_WO : ty == 3 ? TM_WD : rank ? TM_WU : TM_WG];
    const int a1 = ty ? (mp * 2 + rank) * 128 : mp * 128, a2 = ty ? 0 : rank;
    const int b0 = ty ? 0 : idx * 64, b1 = ty ? 0 : rank * 32, b2 = ty == 0 ? 0 : ty == 2 ? idx * 2 : idx * 4 + rank * 2;
    const uint32_t boff = A_BYTES + rank * (ty ? 16384 : 12288), bytes = ty ? STAGE_BYTES : 40960;
    if (ty) mbar_wait(sb + B_ROWDONE, 0);
    const bool duty = (tile >> 26) & 1;
    int ka = ti == 0, kb = ka;
    const uint32_t n0 = n - ka;
    while (true) {
      int avail = nk;
      if (ty) {
        uint32_t known;
        asm volatile("ld.acquire.cta.shared.u32 %0, [%1];" : "=r"(known) : "r"(sb + M_DEP) : "memory");
        avail = min(nk, (((k0 >> sh) + (int)(__shfl_sync(0xffffffffu, known, 0) - base)) << sh) - k0);
        fence_async_all();
      }
#pragma unroll 1
      for (; ka < min(kb, avail); ka++) {
        const uint32_t st = (n0 + ka) & 3;
        asm volatile("{\n.reg .pred p;\nelect.sync _|p, 0xffffffff;\n"
                     "@p cp.async.bulk.tensor.3d.shared::cluster.global.mbarrier::complete_tx::bytes [%0], [%1, {%3, %4, %5}], [%2];\n}"
                     :: "r"(sb + st * STAGE_BYTES), "l"(ta), "r"(sb + B_FULL + 8 * st), "r"(((k0 + ka) & kmask) * 64), "r"(a1), "r"(a2) : "memory");
      }
#pragma unroll 1
      for (; kb < avail; n++) {
        const uint32_t st = n & 3, dst = sb + st * STAGE_BYTES;
        const int kc = ((k0 + kb) & kmask) * 64;
        mbar_wait(sb + B_EMPTY + 8 * st, ((n >> 2) & 1) ^ 1);
        load_stage(sb + B_FULL + 8 * st, bytes, dst + boff, tb, b0, kc + b1, b2, dst, ta, kc, a1, a2);
        mbar_arrive_if(!duty ? sb + B_EMPTY + 8 * st : kb == 3 ? sb + B_DUTY : 0u);
        ka = ++kb;
      }
      if (ka == nk) break;
      const uint32_t st = n & 3;
      if (kb < nk && kb - ka < (ka ? NSTAGE - 1 : NSTAGE) && mbar_test(sb + B_EMPTY + 8 * st, ((n >> 2) & 1) ^ 1)) {
        asm volatile("{\n.reg .pred p;\nelect.sync _|p, 0xffffffff;\n@p mbarrier.arrive.expect_tx.shared::cta.b64 _, [%0], %1;\n"
                     "@p cp.async.bulk.tensor.3d.shared::cluster.global.mbarrier::complete_tx::bytes.multicast::cluster [%2], [%3, {%4, %5, %6}], [%0], %7;\n}"
                     :: "r"(sb + B_FULL + 8 * st), "r"(bytes), "r"(sb + st * STAGE_BYTES + boff), "l"(tb), "r"(b0), "r"(((k0 + kb) & kmask) * 64 + b1), "r"(b2),
                        "h"((uint16_t)3) : "memory");
        mbar_arrive_if(!duty ? sb + B_EMPTY + 8 * st : kb == 3 ? sb + B_DUTY : 0u);
        kb++;
        n++;
      } else {
        __nanosleep(20);
      }
    }
    if (ty) base += t_deps(tile, nk);
  }
}

template <int PITCH>
__device__ __forceinline__ void rows_g2s(uint32_t dst, const void* src, uint32_t bar) {
  asm volatile("{\n.reg .pred p;\nelect.sync _|p, 0xffffffff;\n@p mbarrier.arrive.expect_tx.shared::cta.b64 _, [%2], 8192;\n"
               "@p cp.async.bulk.shared::cluster.global.mbarrier::complete_tx::bytes [%0], [%1], 2048, [%2];\n"
               "@p cp.async.bulk.shared::cluster.global.mbarrier::complete_tx::bytes [%0 + 2048], [%1 + %3], 2048, [%2];\n"
               "@p cp.async.bulk.shared::cluster.global.mbarrier::complete_tx::bytes [%0 + 4096], [%1 + %4], 2048, [%2];\n"
               "@p cp.async.bulk.shared::cluster.global.mbarrier::complete_tx::bytes [%0 + 6144], [%1 + %5], 2048, [%2];\n}"
               :: "r"(dst), "l"(src), "r"(bar), "n"(PITCH), "n"(2 * PITCH), "n"(3 * PITCH) : "memory");
}
__device__ __forceinline__ void sum_sq8(const uint4& v, float& s, float& qq) {
  const float a0 = bf_lo(v.x), b0 = bf_hi(v.x), a1 = bf_lo(v.y), b1 = bf_hi(v.y), a2 = bf_lo(v.z), b2 = bf_hi(v.z), a3 = bf_lo(v.w), b3 = bf_hi(v.w);
  s += ((a0 + b0) + (a1 + b1)) + ((a2 + b2) + (a3 + b3));
  qq += fmaf(a0, a0, fmaf(b0, b0, fmaf(a1, a1, b1 * b1))) + fmaf(a2, a2, fmaf(b2, b2, fmaf(a3, a3, b3 * b3)));
}
__device__ __forceinline__ float inv_std(float s, float qq) {
  const float mu = s * (1.f / DM);
  return rsqrtf(fmaxf(qq * (1.f / DM) - mu * mu, 0.f) + 1e-5f);
}

__device__ __forceinline__ void x_rows(const Params& p, uint32_t sb, int w) {
  const int l = threadIdx.x & 31;
  if (blockIdx.x < 128) {
    const int row0 = blockIdx.x * 8 + w;
    const uint32_t bar = sb + B_ROW + 16 * w;
    uint32_t reg = sb + (2 * w + 1) * STAGE_BYTES - 8192;
    mbar_wait(sb + B_GO, 0);
    rows_g2s<4096>(reg, p.x + (size_t)row0 * DM, bar);
    const uint32_t tag = get_epoch(sb);
#pragma unroll 1
    for (int pass = 0; pass < 2; pass++) {
      mbar_wait(bar + 8 * pass, 0);
      float s = 0.f, qq = 0.f;
      const uint32_t src = reg + (l >> 3) * 2048 + (l & 7) * 16;
#pragma unroll 1
      for (int u = 0; u < 2048; u += 512) {
        if (pass == 0 && u == 1024) rows_g2s<4096>(reg + STAGE_BYTES, p.x + (size_t)(1024 + row0) * DM, bar + 8);
        uint4 v[4];
#pragma unroll
        for (int i = 0; i < 4; i++) v[i] = lds128(src + u + i * 128);
        sched_fence(sb);
#pragma unroll
        for (int i = 0; i < 4; i++) sum_sq8(v[i], s, qq);
      }
#pragma unroll
      for (int o = 1; o < 8; o <<= 1) { s += __shfl_xor_sync(0xffffffffu, s, o); qq += __shfl_xor_sync(0xffffffffu, qq, o); }
      const int o = w * 1024 + pass * 512 + blockIdx.x * 4 + (l >> 3);
      st_gpu64_if((l & 7) == 0, g_xst + 8 + o, asu(s * (1.f / DM)), tagged(inv_std(s, qq), tag));
#pragma unroll 1
      for (int i = 0; i < 4; i++) {
        asm volatile("{\n.reg .pred p;\nelect.sync _|p, 0xffffffff;\n@p cp.async.bulk.global.shared::cta.bulk_group [%0], [%1], 2048;\n}"
                     :: "l"(p.out + (size_t)(pass * 1024 + row0 + 2 * i) * DM), "r"(reg + i * 2048) : "memory");
        bulk_commit();
        bulk_wait_read<0>();
      }
      reg += STAGE_BYTES;
    }
    bulk_wait_all();
  }
  __syncwarp();
  asm volatile("{\n.reg .pred p;\nsetp.lt.u32 p, %1, 2;\n@p mbarrier.arrive.shared::cluster.b64 _, [%0];\n}"
               :: "r"(mapa(sb + B_ROWDONE, l & 1)), "r"(l) : "memory");
}

__device__ __forceinline__ void wo_rows(const Params& p, uint32_t sb, uint32_t tag) {
  const int l = threadIdx.x & 31, row = l >> 2;
  mbar_wait(sb + B_GO + 8, 0);
  rows_g2s<2048>(sb + OFF_STG + 8192, p.wo + (size_t)blockIdx.x * 8 * DM, sb + B_ROW + 32);
  rows_g2s<2048>(sb + OFF_STG + 24576, p.wo + (size_t)(blockIdx.x * 8 + 4) * DM, sb + B_ROW + 32);
  mbar_wait(sb + B_ROW + 32, 0);
  const uint32_t src = sb + OFF_STG + 8192 + (row >> 2) * 16384 + (row & 3) * 2048 + (row & 1) * 64 + (l & 3) * 16;
  float s = 0.f;
#pragma unroll 1
  for (int u = 0; u < 2048; u += 256) {
    const uint4 v[4] = {lds128(src + u), lds128((src ^ 64) + u), lds128(src + u + 128), lds128((src ^ 64) + u + 128)};
    sched_fence(sb);
#pragma unroll
    for (int i = 0; i < 4; i++) {
      const uint32_t a = add2(v[i].x, v[i].y), b = add2(v[i].z, v[i].w);
      s += (bf_lo(a) + bf_hi(a)) + (bf_lo(b) + bf_hi(b));
    }
  }
  s = quad_sum(s);
  st_gpu64_if((l & 3) == 0, g_rm + blockIdx.x * 8 + row, asu(s * (1.f / DM)), tag);
}

__device__ __forceinline__ void aux_warp(const Params& p, uint32_t sb, int rank, int pair) {
  const int l = threadIdx.x & 31;
  const uint32_t ep = get_epoch(sb);
  mbar_wait(sb + B_ROWDONE, 0);
  if (blockIdx.x < 128) flag_add(l ? nullptr : g_flags + FL_COPY, 1);
  while (true) {
    if (__all_sync(0xffffffffu, flag_set(false, g_flags + FL_COPY, ep * 128))) break;
    __nanosleep(200);
  }
  fence_async_all();
  mbar_arrive_warp(sb + B_COPY);
  const uint32_t* sched = p.sched + pair * MAXT;
  uint32_t n = 0, ph = 0;
  for (int ti = 0;; ti++) {
    const uint32_t tile = __shfl_sync(0xffffffffu, sched[ti], 0);
    if (tile == TILE_END) break;
    if ((tile >> 26) & 1) {
      const int wide = (tile >> 23) & 1, row = ((tile >> 27) & 7) * 16 + (l >> (1 - wide));
      const uint32_t src = sb + row * 128, half = wide ? (row >> 2) & 1 : l & 1;
      float s = 0.f, qq = 0.f;
      mbar_wait(sb + B_DUTY, ph);
      ph ^= 1;
#pragma unroll 1
      for (uint32_t k = n; k < n + 16; k++) {
        const uint32_t st = k & 3;
        mbar_wait(sb + B_FULL + 8 * st, (k >> 2) & 1);
#pragma unroll 1
        for (int j = wide; j >= 0; j--) {
          uint4 v[4];
#pragma unroll
          for (int i = 0; i < 4; i++) v[i] = lds128(src + st * STAGE_BYTES + (half ^ j) * 64 + (((i + row) & 3) << 4));
          mbar_arrive_if(j ? 0u : sb + B_EMPTY + 8 * st);
#pragma unroll
          for (int i = 0; i < 4; i++) {
            const uint32_t t = fma2(v[i].w, v[i].w, fma2(v[i].z, v[i].z, fma2(v[i].y, v[i].y, mul2(v[i].x, v[i].x))));
            s += bf_lo(t); qq += bf_hi(t);
          }
        }
      }
      qq += s;
      if (!wide) qq += __shfl_xor_sync(0xffffffffu, qq, 1);
      st_gpu32_if(wide || !(l & 1), g_hrs + (t_mp(tile) * 2 + rank) * 128 + row, tagged(inv_std(0.f, qq), ep));
    }
    n += t_nk(tile);
  }
}

__device__ __forceinline__ void io_warp(const Params& p, uint32_t sb, int rank, int pair) {
  const uint32_t* sched = p.sched + pair * MAXT;
  const int l = threadIdx.x & 31;
  uint32_t phb = 0;
  uint32_t steps = 0;
  const uint32_t ep = get_epoch(sb);
  if (blockIdx.x < 128) wo_rows(p, sb, ep);
  for (int ti = 0;; ti++) {
    const uint32_t tile = __shfl_sync(0xffffffffu, sched[ti], 0);
    if (tile == TILE_END) break;
    const int ty = t_type(tile), mp = t_mp(tile), idx = t_idx(tile);
    if (ty == 0) {
      if (ti == 0) {
        const uint4* src = (const uint4*)(g_rm + idx * 64) + l;
        uint4 e;
        while (true) {
          e = ld_gpu128(src);
          if (!__any_sync(0xffffffffu, e.y != ep || e.w != ep)) break;
          __nanosleep(100);
        }
        const uint32_t dst = sb + M_RM + (l >> 4) * 128 + (l & 3) * 32 + ((l >> 2) & 3) * 4;
        asm volatile("st.shared.u32 [%0], %1;\nst.shared.u32 [%0 + 16], %2;" :: "r"(dst), "r"(e.x), "r"(e.z) : "memory");
        mbar_arrive_warp(sb + B_RM);
      }
      uint4* box = g_halo + ((mp * 2 - 2 + rank) * 16 + idx) * 128 + l;
      uint4 v[4];
#pragma unroll
      for (int i = 0; i < 4; i++) v[i] = make_uint4(~0u, ~0u, ~0u, ~0u);
      if (mp) {
        while (true) {
          uint32_t least = ~0u;
#pragma unroll
          for (int i = 0; i < 4; i++) v[i] = ld_gpu128(box + i * 32);
#pragma unroll
          for (int i = 0; i < 4; i++) least = min(min(least, min(v[i].x, v[i].y)), min(v[i].z, v[i].w));
          if (!__any_sync(0xffffffffu, least == 0)) break;
          mbar_wait(sb + B_CS, (phb >> 2) & 1);
        }
      }
      phb ^= 4;
#pragma unroll
      for (int i = 0; i < 4; i++) stsm4(sb + OFF_STG + i * 512 + l * 16, ~v[i].x, ~v[i].y, ~v[i].z, ~v[i].w);
      mbar_arrive_warp(sb + B_HALO);
#pragma unroll
      for (int i = 0; i < 4; i++) st_gpu128_if(mp, box + i * 32, 0u, 0u, 0u, 0u);
    } else if (ty == 1) {
      mbar_wait(sb + B_COPY, 0);
    } else if (ty == 3) {
      const uint32_t* flag = g_flags + FL_OUT + (16 + mp) * 32 + l;
      bool ok = l >= 28;
      while (true) {
        ok = flag_set(ok, flag, ep * 32);
        if (__all_sync(0xffffffffu, ok)) break;
        __nanosleep(FLAG_SLEEP);
      }
      fence_async_all();
      if (sched[ti + 1] == TILE_END) {
        mbar_arrive_warp(sb + B_GATE);
        break;
      }
    }
    const int split = (tile >> 24) & ty & 1;
    const bool early = (tile >> 25) & 1;
    const int n = ty == 0 ? 2 : ty == 2 ? 4 : 8, col0 = idx * (n * 32), row0 = ty == 0 ? mp * 128 : (mp * 2 + rank) * 128;
    uint32_t* done = g_flags + FL_OUT + (ty * 8 + mp) * 32 + (ty == 1 ? idx * 2 + 1 : idx);
    const CUtensorMap* tm = &p.tm[ty == 0 ? TM_ATTN_ST : ty == 2 ? TM_ACT_ST : TM_OUT_ST];
    uint32_t before = 0;
    steps += t_nk(tile);
    if (split) {
      mbar_wait(sb + B_HALF, (phb >> 3) & 1);
      phb ^= 8 + 3;
      if (early) flag_add(l ? nullptr : done - 1, t_nk(tile));
    }
#pragma unroll 1
    for (int i = split * 5; i < n; i += 1 + split) {
      const int w = i & 1, ch = i >> 1, sub = ch & 1;
      mbar_wait(sb + B_OUTF + w * 16 + sub * 8, ((phb >> sub) ^ (i >> 2)) & 1);
      const uint32_t src = sb + OFF_STG + w * 16384 + sub * 8192;
      if (ty & 1) tma_add3d(tm, src, col0 + ch * 64, row0 + w * 64, 0);
      else tma_st3d(tm, src, col0 + ch * 64, row0 + w * 64, ty == 0 ? rank : 0);
      bulk_commit();
      bulk_wait_read<1>();
      if (before) mbar_arrive_warp(before);
      before = sb + B_OUTE + w * 16 + sub * 8;
    }
    if (split) {
      mbar_wait(sb + B_OUTF + 8, ((phb >> 1) & 1) ^ 1);
      mbar_arrive_warp(sb + B_OUTE);
      mbar_arrive_warp(sb + B_OUTE + 8);
    }
    phb ^= n == 2 ? 1 : n == 4 ? 3 : 0;
    bulk_wait_all();
    mbar_arrive_warp(before);
    if (ty != 3) flag_add(l == 0 ? done : ty == 1 && l == 1 && !early ? done - 1 : nullptr, t_nk(tile));
    asm volatile("{\n.reg .pred p;\nsetp.ne.u32 p, %1, 0;\n@p mbarrier.arrive.shared::cluster.b64 _, [%0];\n}"
                 :: "r"(mapa(sb + B_EMPTY + 8 * ((steps + 1 + (l >> 1)) & 3), l & 1)), "r"((uint32_t)(early && l < 2 * TAIL)) : "memory");
  }
}

__global__ void __cluster_dims__(2, 1, 1) __launch_bounds__(384, 1) fused_block_kernel(const __grid_constant__ Params p) {
  extern __shared__ __align__(1024) uint8_t smem_raw[];
  uint32_t sb = (uint32_t)__cvta_generic_to_shared(smem_raw);
  asm volatile("" : "+r"(sb));
  sb = __shfl_sync(0xffffffffu, sb, 0);
  const int wg = __shfl_sync(0xffffffffu, threadIdx.x >> 7, 0);
  const int rank = __shfl_sync(0xffffffffu, blockIdx.x & 1, 0), pair = __shfl_sync(0xffffffffu, blockIdx.x >> 1, 0);
  const int warp = __shfl_sync(0xffffffffu, threadIdx.x >> 5, 0) - 8;
  if (warp == 0) {
    const uint32_t t0 = (pair >> 4) << 2 | (pair & 15) << 5;
    const int kc = p1_k(t_mp(t0), 0) * 64;
    asm volatile("{\n.reg .pred p;\nelect.sync _|p, 0xffffffff;\n"
                 "@p mbarrier.init.shared::cta.b64 [%0], 1;\nfence.mbarrier_init.release.cluster;\nfence.proxy.async.shared::cta;\n"
                 "@p mbarrier.arrive.expect_tx.shared::cta.b64 _, [%0], 40960;\n"
                 "@p cp.async.bulk.tensor.3d.shared::cluster.global.mbarrier::complete_tx::bytes [%1 + 16384], [%2, {%4, %5, %9}], [%0];\n"
                 "@p cp.async.bulk.tensor.3d.shared::cluster.global.mbarrier::complete_tx::bytes [%1], [%3, {%5, %7, %8}], [%0];\n"
                 "@p cp.async.bulk.tensor.3d.shared::cluster.global.mbarrier::complete_tx::bytes [%1 + 28672], [%2, {%4, %6, %9}], [%0];\n}"
                 :: "r"(sb + B_FULL), "r"(sb), "l"(&p.tm[TM_WQKV]), "l"(&p.tm[TM_X1]), "r"(t_idx(t0) * 64), "r"(kc), "r"(kc + 32),
                    "r"(t_mp(t0) * 128), "r"(rank), "r"(0) : "memory");
  }
  if (threadIdx.x == 0) {
#pragma unroll
    for (int i = 0; i < 4; i++) {
      if (i) mbar_init(sb + B_FULL + 8 * i, 1);
      mbar_init(sb + B_EMPTY + 8 * i, 5); mbar_init(sb + B_OUTF + 8 * i, 4); mbar_init(sb + B_OUTE + 8 * i, 1); mbar_init(sb + B_ROW + 8 * i, 1);
    }
    mbar_init(sb + B_HALO, 4); mbar_init(sb + B_HALO + 8, 4); mbar_init(sb + B_RM, 1); mbar_init(sb + B_EPOCH, 1);
    mbar_init(sb + B_CS, 8); mbar_init(sb + B_ROWDONE, 4); mbar_init(sb + B_ROW + 32, 2); mbar_init(sb + B_GATE, 1); mbar_init(sb + B_COPY, 1); mbar_init(sb + B_DUMP, 8); mbar_init(sb + B_HALF, 8);
    mbar_init(sb + B_GO, 8); mbar_init(sb + B_GO + 8, 8); mbar_init(sb + B_DUTY, 1);
    asm volatile("st.shared.u32 [%0], %1;" :: "r"(sb + M_DEP), "r"(0) : "memory");
    asm volatile("fence.mbarrier_init.release.cluster;" ::: "memory");
    fence_async_smem();
  }
  if (threadIdx.x >= 32 && threadIdx.x < 56) asm volatile("st.shared.u32 [%0], %1;" :: "r"(sb + M_CS + 640 + threadIdx.x * 4), "r"(0) : "memory");
  __syncthreads();
  asm volatile("barrier.cluster.arrive.relaxed.aligned;\nbarrier.cluster.wait.aligned;" ::: "memory");
  if (wg < 2) {
    asm volatile("setmaxnreg.inc.sync.aligned.u32 224;");
    consumer(p, sb, wg, rank, pair);
  } else {
    asm volatile("setmaxnreg.dec.sync.aligned.u32 56;");
    if (warp > 0) {
      if (threadIdx.x == 289) {
        const uint32_t e = atomicAdd(g_flags + FL_LAUNCH, 1u) / (uint32_t)p.ncta + 1;
        asm volatile("st.shared.u32 [%0], %1;" :: "r"(sb + M_EPOCH), "r"(e) : "memory");
        mbar_arrive(sb + B_EPOCH);
#pragma unroll
        for (int i = TM_ATTN_ST; i < TM_COUNT; i++) asm volatile("prefetch.tensormap [%0];" :: "l"(&p.tm[i]) : "memory");
      }
      __syncwarp();
      if (warp == 1) {
        io_warp(p, sb, rank, pair);
      } else {
        x_rows(p, sb, warp - 2);
        if (warp == 2) aux_warp(p, sb, rank, pair);
        else watcher(p, sb, pair);
      }
    } else {
      producer(p, sb, rank, pair);
    }
  }
}

typedef CUresult (*EncodeFn)(CUtensorMap*, CUtensorMapDataType, cuuint32_t, void*, const cuuint64_t*, const cuuint64_t*, const cuuint32_t*,
                             const cuuint32_t*, CUtensorMapInterleave, CUtensorMapSwizzle, CUtensorMapL2promotion, CUtensorMapFloatOOBfill);

void encode(EncodeFn fn, CUtensorMap* m, const void* ptr, uint64_t d0, uint64_t d1, uint64_t d2, uint64_t s1, uint64_t s2,
            uint32_t b0, uint32_t b1, uint32_t b2) {
  const cuuint64_t dims[3] = {d0, d1, d2}, strides[2] = {s1, s2};
  const cuuint32_t box[3] = {b0, b1, b2}, es[3] = {1, 1, 1};
  fn(m, CU_TENSOR_MAP_DATA_TYPE_BFLOAT16, 3, (void*)ptr, dims, strides, box, es, CU_TENSOR_MAP_INTERLEAVE_NONE,
     CU_TENSOR_MAP_SWIZZLE_128B, CU_TENSOR_MAP_L2_PROMOTION_L2_128B, CU_TENSOR_MAP_FLOAT_OOB_FILL_NONE);
}

const uint32_t kSchedule[MAXPAIRS * MAXT] = {
  0x01100000, 0x0110001c, 0x00500051, 0x011002c6, 0x7490001e, 0x0010031e, 0x004d6417, 0x010a5c07, TILE_END, TILE_END, TILE_END, TILE_END, TILE_END, TILE_END, TILE_END, TILE_END,
  0x01100020, 0x0010003c, 0x40100062, 0x401000ee, 0x74100092, 0x00100176, 0x01190017, TILE_END, TILE_END, TILE_END, TILE_END, TILE_END, TILE_END, TILE_END, TILE_END, TILE_END,
  0x01100040, 0x0010005c, 0x7c100102, 0x4010032e, 0x6c100216, 0x00100116, 0x011a006b, TILE_END, TILE_END, TILE_END, TILE_END, TILE_END, TILE_END, TILE_END, TILE_END, TILE_END,
  0x01100060, 0x0010007c, 0x40100142, 0x401000ae, 0x6c100232, 0x001001be, 0x011a0077, TILE_END, TILE_END, TILE_END, TILE_END, TILE_END, TILE_END, TILE_END, TILE_END, TILE_END,
  0x01100080, 0x00100098, 0x40100362, 0x401001ce, 0x40100272, 0x001001de, 0x011a7873, TILE_END, TILE_END, TILE_END, TILE_END, TILE_END, TILE_END, TILE_END, TILE_END, TILE_END,
  0x011000a0, 0x001000bc, 0x401000a2, 0x4010034e, 0x40100236, 0x00558c6f, 0x01158c1f, TILE_END, TILE_END, TILE_END, TILE_END, TILE_END, TILE_END, TILE_END, TILE_END, TILE_END,
  0x011000c0, 0x001000dc, 0x40100162, 0x4010006e, 0x401000b2, 0x004cb02f, 0x015e0073, TILE_END, TILE_END, TILE_END, TILE_END, TILE_END, TILE_END, TILE_END, TILE_END, TILE_END,
  0x011000e0, 0x03042001, 0x54100242, 0x00500079, 0x5c100052, 0x00550043, 0x0156885b, TILE_END, TILE_END, TILE_END, TILE_END, TILE_END, TILE_END, TILE_END, TILE_END, TILE_END,
  0x01100100, 0x01043021, 0x03062805, 0x441000e6, 0x5410002a, 0x0010013e, 0x000c0063, 0x0157001f, TILE_END, TILE_END, TILE_END, TILE_END, TILE_END, TILE_END, TILE_END, TILE_END,
  0x01100120, 0x03470021, 0x00500015, 0x00100346, 0x4010029e, 0x00100312, 0x0156005f, TILE_END, TILE_END, TILE_END, TILE_END, TILE_END, TILE_END, TILE_END, TILE_END, TILE_END,
  0x01100140, 0x00100158, 0x401001e2, 0x4010018e, 0x40100096, 0x001002f2, 0x000d5443, 0x010d541b, TILE_END, TILE_END, TILE_END, TILE_END, TILE_END, TILE_END, TILE_END, TILE_END,
  0x01100160, 0x0010017c, 0x40100342, 0x401001ae, 0x401000d2, 0x001001da, 0x000dac43, 0x010d6837, TILE_END, TILE_END, TILE_END, TILE_END, TILE_END, TILE_END, TILE_END, TILE_END,
  0x01100180, 0x03041001, 0x0146280d, 0x4c100106, 0x5c10004a, 0x4c10027a, 0x0010033a, 0x01129817, TILE_END, TILE_END, TILE_END, TILE_END, TILE_END, TILE_END, TILE_END, TILE_END,
  0x011001a0, 0x001001b8, 0x401002c2, 0x4010004e, 0x401001d6, 0x001000ba, 0x000d686b, 0x010d000f, TILE_END, TILE_END, TILE_END, TILE_END, TILE_END, TILE_END, TILE_END, TILE_END,
  0x011001c0, 0x001001d8, 0x401002e2, 0x4010012e, 0x40100256, 0x001002fa, 0x004c002b, 0x010e0067, TILE_END, TILE_END, TILE_END, TILE_END, TILE_END, TILE_END, TILE_END, TILE_END,
  0x011001e0, 0x034a0005, 0x6c100046, 0x7c10012a, 0x0010027e, 0x000f340f, 0x0114907f, TILE_END, TILE_END, TILE_END, TILE_END, TILE_END, TILE_END, TILE_END, TILE_END, TILE_END,
  0x01100004, 0x014c1061, 0x00500055, 0x00100366, 0x4010025e, 0x0165004f, TILE_END, TILE_END, TILE_END, TILE_END, TILE_END, TILE_END, TILE_END, TILE_END, TILE_END, TILE_END,
  0x01100024, 0x01051c21, 0x01072425, 0x64100006, 0x7410000a, 0x5c10013a, 0x0010033e, 0x0113944f, TILE_END, TILE_END, TILE_END, TILE_END, TILE_END, TILE_END, TILE_END, TILE_END,
  0x01100044, 0x01100054, 0x00500011, 0x00100326, 0x5490023e, 0x0010011e, 0x0158007f, TILE_END, TILE_END, TILE_END, TILE_END, TILE_END, TILE_END, TILE_END, TILE_END, TILE_END,
  0x01100064, 0x01100074, 0x00500071, 0x00100306, 0x4490003e, 0x0010031a, 0x01578407, TILE_END, TILE_END, TILE_END, TILE_END, TILE_END, TILE_END, TILE_END, TILE_END, TILE_END,
  0x01100084, 0x0010009c, 0x40100222, 0x4010020e, 0x401000b6, 0x01290003, TILE_END, TILE_END, TILE_END, TILE_END, TILE_END, TILE_END, TILE_END, TILE_END, TILE_END, TILE_END,
  0x001000a4, 0x001000b8, 0x6c100262, 0x6c10000e, 0x64100036, 0x001002d2, 0x0050a04b, 0x010a5057, TILE_END, TILE_END, TILE_END, TILE_END, TILE_END, TILE_END, TILE_END, TILE_END,
  0x001000c4, 0x011000d0, 0x40100122, 0x4010002e, 0x7c100212, 0x00100136, 0x011a0027, TILE_END, TILE_END, TILE_END, TILE_END, TILE_END, TILE_END, TILE_END, TILE_END, TILE_END,
  0x001000e4, 0x011000f0, 0x0105000d, 0x74100126, 0x4010014a, 0x0010007e, 0x00100332, 0x0153943f, TILE_END, TILE_END, TILE_END, TILE_END, TILE_END, TILE_END, TILE_END, TILE_END,
  0x00100104, 0x00100118, 0x0008002d, 0x40100166, 0x4010016a, 0x001000f2, 0x0123302b, TILE_END, TILE_END, TILE_END, TILE_END, TILE_END, TILE_END, TILE_END, TILE_END, TILE_END,
  0x00100124, 0x00100134, 0x0110013c, 0x00100266, 0x44100012, 0x00100356, 0x0110021a, 0x010cb00f, TILE_END, TILE_END, TILE_END, TILE_END, TILE_END, TILE_END, TILE_END, TILE_END,
  0x01100144, 0x0010015c, 0x40100202, 0x401001ee, 0x40100316, 0x001000da, 0x000d004b, 0x010c607f, TILE_END, TILE_END, TILE_END, TILE_END, TILE_END, TILE_END, TILE_END, TILE_END,
  0x00100164, 0x00100178, 0x40100182, 0x7c1002ae, 0x741002b6, 0x00100156, 0x011a0023, TILE_END, TILE_END, TILE_END, TILE_END, TILE_END, TILE_END, TILE_END, TILE_END, TILE_END,
  0x00100184, 0x00100190, 0x00080009, 0x7c1001c6, 0x401001ea, 0x6410023a, 0x00100352, 0x0153943b, TILE_END, TILE_END, TILE_END, TILE_END, TILE_END, TILE_END, TILE_END, TILE_END,
  0x001001a4, 0x001001b0, 0x001001bc, 0x0050003d, 0x0010024a, 0x001002ba, 0x015e6823, TILE_END, TILE_END, TILE_END, TILE_END, TILE_END, TILE_END, TILE_END, TILE_END, TILE_END,
  0x011001c4, 0x03443001, 0x441000c2, 0x4c1002ce, 0x4c100016, 0x00583063, 0x0113007b, TILE_END, TILE_END, TILE_END, TILE_END, TILE_END, TILE_END, TILE_END, TILE_END, TILE_END,
  0x001001e4, 0x001001f4, 0x001001fc, 0x0050005d, 0x0010032a, 0x001002b2, 0x011000fa, 0x010c5c1f, TILE_END, TILE_END, TILE_END, TILE_END, TILE_END, TILE_END, TILE_END, TILE_END,
  0x00100008, 0x01100014, 0x401002a2, 0x4010028e, 0x40100072, 0x001001ba, 0x00519c37, 0x0109002f, TILE_END, TILE_END, TILE_END, TILE_END, TILE_END, TILE_END, TILE_END, TILE_END,
  0x00100028, 0x00100038, 0x00500069, 0x4410022e, 0x44100276, 0x00100376, 0x00529877, 0x01098843, TILE_END, TILE_END, TILE_END, TILE_END, TILE_END, TILE_END, TILE_END, TILE_END,
  0x00100048, 0x00100058, 0x401001c2, 0x4010014e, 0x40100252, 0x00149063, 0x0156881b, TILE_END, TILE_END, TILE_END, TILE_END, TILE_END, TILE_END, TILE_END, TILE_END, TILE_END,
  0x00100068, 0x01100070, 0x40100302, 0x4010036e, 0x401002d6, 0x00100152, 0x011a0037, TILE_END, TILE_END, TILE_END, TILE_END, TILE_END, TILE_END, TILE_END, TILE_END, TILE_END,
  0x00100088, 0x01100094, 0x00500031, 0x011002e6, 0x6490017e, 0x00100172, 0x01170007, TILE_END, TILE_END, TILE_END, TILE_END, TILE_END, TILE_END, TILE_END, TILE_END, TILE_END,
  0x001000a8, 0x001000b4, 0x0008006d, 0x40100146, 0x4010026a, 0x7410015a, 0x004fa403, 0x01140057, TILE_END, TILE_END, TILE_END, TILE_END, TILE_END, TILE_END, TILE_END, TILE_END,
  0x001000c8, 0x001000d4, 0x00482009, 0x401000c6, 0x4010008a, 0x00100292, 0x0010035e, 0x0112005b, TILE_END, TILE_END, TILE_END, TILE_END, TILE_END, TILE_END, TILE_END, TILE_END,
  0x001000e8, 0x001000f4, 0x011000fc, 0x00100286, 0x0010036a, 0x0010019e, 0x015d0033, TILE_END, TILE_END, TILE_END, TILE_END, TILE_END, TILE_END, TILE_END, TILE_END, TILE_END,
  0x00100108, 0x00100110, 0x0048204d, 0x401000a6, 0x4010006a, 0x7c10001a, 0x0123242f, TILE_END, TILE_END, TILE_END, TILE_END, TILE_END, TILE_END, TILE_END, TILE_END, TILE_END,
  0x00100128, 0x00100130, 0x0048206d, 0x401001e6, 0x401000aa, 0x4010007a, 0x0010037e, 0x0112003b, TILE_END, TILE_END, TILE_END, TILE_END, TILE_END, TILE_END, TILE_END, TILE_END,
  0x00100148, 0x00100150, 0x00482065, 0x40100246, 0x401002ea, 0x4010025a, 0x0010037a, 0x0112003f, TILE_END, TILE_END, TILE_END, TILE_END, TILE_END, TILE_END, TILE_END, TILE_END,
  0x00100168, 0x00100174, 0x01080045, 0x01500019, 0x0010022a, 0x00100112, 0x004c000b, 0x0113483b, TILE_END, TILE_END, TILE_END, TILE_END, TILE_END, TILE_END, TILE_END, TILE_END,
  0x00100188, 0x00100194, 0x00080065, 0x40100086, 0x401001aa, 0x0010015e, 0x0010021e, 0x0153947b, TILE_END, TILE_END, TILE_END, TILE_END, TILE_END, TILE_END, TILE_END, TILE_END,
  0x011001a8, 0x03040001, 0x4c100002, 0x5410024e, 0x541001f6, 0x001000f6, 0x011b7433, TILE_END, TILE_END, TILE_END, TILE_END, TILE_END, TILE_END, TILE_END, TILE_END, TILE_END,
  0x001001c8, 0x001001d0, 0x001001dc, 0x00500059, 0x0010030a, 0x001000be, 0x015e6827, TILE_END, TILE_END, TILE_END, TILE_END, TILE_END, TILE_END, TILE_END, TILE_END, TILE_END,
  0x001001e8, 0x001001f8, 0x00080049, 0x40100066, 0x4010028a, 0x6c10005a, 0x0123300b, TILE_END, TILE_END, TILE_END, TILE_END, TILE_END, TILE_END, TILE_END, TILE_END, TILE_END,
  0x0010000c, 0x00100018, 0x0048202d, 0x401001a6, 0x4010018a, 0x4010017a, 0x0010035a, 0x01132853, TILE_END, TILE_END, TILE_END, TILE_END, TILE_END, TILE_END, TILE_END, TILE_END,
  0x0010002c, 0x01100034, 0x401001a2, 0x4010010e, 0x40100076, 0x001002fe, 0x015a7857, TILE_END, TILE_END, TILE_END, TILE_END, TILE_END, TILE_END, TILE_END, TILE_END, TILE_END,
  0x0010004c, 0x01100050, 0x01040061, 0x00500075, 0x441000ea, 0x0010005e, 0x001001fe, 0x0115001b, TILE_END, TILE_END, TILE_END, TILE_END, TILE_END, TILE_END, TILE_END, TILE_END,
  0x0010006c, 0x00100078, 0x40100322, 0x4010016e, 0x401002f6, 0x001000fe, 0x0050700f, 0x010a0053, TILE_END, TILE_END, TILE_END, TILE_END, TILE_END, TILE_END, TILE_END, TILE_END,
  0x0010008c, 0x01100090, 0x40100282, 0x401000ce, 0x401001b6, 0x005a0047, 0x0110485b, TILE_END, TILE_END, TILE_END, TILE_END, TILE_END, TILE_END, TILE_END, TILE_END, TILE_END,
  0x001000ac, 0x011000b0, 0x0105140d, 0x54100026, 0x6c10010a, 0x5410003a, 0x00100192, 0x0113945f, TILE_END, TILE_END, TILE_END, TILE_END, TILE_END, TILE_END, TILE_END, TILE_END,
  0x001000cc, 0x001000d8, 0x641000e2, 0x641002ee, 0x641001f2, 0x00100132, 0x011b7413, TILE_END, TILE_END, TILE_END, TILE_END, TILE_END, TILE_END, TILE_END, TILE_END, TILE_END,
  0x001000ec, 0x001000f8, 0x0008004d, 0x40100186, 0x401001ca, 0x0010009e, 0x0010011a, 0x01124c7b, TILE_END, TILE_END, TILE_END, TILE_END, TILE_END, TILE_END, TILE_END, TILE_END,
  0x0010010c, 0x00100114, 0x0110011c, 0x001002a6, 0x4c100032, 0x0010009a, 0x015d0013, TILE_END, TILE_END, TILE_END, TILE_END, TILE_END, TILE_END, TILE_END, TILE_END, TILE_END,
  0x0010012c, 0x00100138, 0x00482049, 0x40100226, 0x401002ca, 0x00100336, 0x001001b2, 0x0113483f, TILE_END, TILE_END, TILE_END, TILE_END, TILE_END, TILE_END, TILE_END, TILE_END,
  0x0010014c, 0x00100154, 0x01482045, 0x0150001d, 0x0010020a, 0x001000d6, 0x00100372, 0x010f585f, TILE_END, TILE_END, TILE_END, TILE_END, TILE_END, TILE_END, TILE_END, TILE_END,
  0x0010016c, 0x00100170, 0x74100042, 0x7410030e, 0x7c100196, 0x001000de, 0x00519c6b, 0x0109bc0b, TILE_END, TILE_END, TILE_END, TILE_END, TILE_END, TILE_END, TILE_END, TILE_END,
  0x0010018c, 0x00100198, 0x0010019c, 0x00500039, 0x0010034a, 0x0010019a, 0x011e6847, TILE_END, TILE_END, TILE_END, TILE_END, TILE_END, TILE_END, TILE_END, TILE_END, TILE_END,
  0x001001ac, 0x001001b4, 0x5c100022, 0x5c10026e, 0x5c100296, 0x001002da, 0x015b7453, TILE_END, TILE_END, TILE_END, TILE_END, TILE_END, TILE_END, TILE_END, TILE_END, TILE_END,
  0x001001cc, 0x001001d4, 0x40100082, 0x4010008e, 0x40100056, 0x016a3867, TILE_END, TILE_END, TILE_END, TILE_END, TILE_END, TILE_END, TILE_END, TILE_END, TILE_END, TILE_END,
  0x001001ec, 0x001001f0, 0x00500029, 0x0050007d, 0x541001d2, 0x001002de, 0x011b344b, TILE_END, TILE_END, TILE_END, TILE_END, TILE_END, TILE_END, TILE_END, TILE_END, TILE_END,
  0x01100010, 0x00040041, 0x01490025, 0x00500035, 0x4c1000ca, 0x001002be, 0x001001fa, 0x000c6877, 0x0109bc2b, TILE_END, TILE_END, TILE_END, TILE_END, TILE_END, TILE_END, TILE_END,
  0x01100030, 0x034c1041, 0x5c100206, 0x641002aa, 0x4410029a, 0x0123006f, TILE_END, TILE_END, TILE_END, TILE_END, TILE_END, TILE_END, TILE_END, TILE_END, TILE_END, TILE_END,
};

int build_schedule(uint32_t* sched) {
  memcpy(sched, kSchedule, sizeof(kSchedule));
  for (int i = 0; i < MAXPAIRS * MAXT; i++) {
    const uint32_t t = sched[i];
    if (t == TILE_END) continue;
    const uint32_t u = sched[i + 1], ty = t & 3;
    if (u == TILE_END || (ty && !(u & 3)) || (int)((u >> 16) & 63) < (ty == 0 ? DEF_AW : ty == 2 ? DEF_G + ((t >> 30) & 1) : DEF_R) + TAIL) sched[i] |= 1u << 24;
  }
  return MAXPAIRS;
}

}

extern "C" void kernel_launch(void* const* d_in, const int* in_sizes, int n_in, void* d_out, int out_size) {
  static Params p;
  static void* seen[7];
  if (p.out != d_out || memcmp(seen, d_in, sizeof(seen))) {
    memcpy(seen, d_in, sizeof(seen));
    void* fnp = nullptr;
    cudaDriverEntryPointQueryResult qr;
    cudaGetDriverEntryPoint("cuTensorMapEncodeTiled", &fnp, cudaEnableDefault, &qr);
    EncodeFn fn = (EncodeFn)fnp;
    p.x = (const __nv_bfloat16*)d_in[0];
    p.wo = (const __nv_bfloat16*)d_in[2];
    p.out = (__nv_bfloat16*)d_out;
    void *attn, *act;
    cudaGetSymbolAddress(&attn, g_attn);
    cudaGetSymbolAddress(&act, g_act);
    encode(fn, &p.tm[TM_X1], p.x, DM, S_LEN / 2, 2, DM * 4, DM * 2, 64, 128, 1);
    encode(fn, &p.tm[TM_ATTN_ST], attn, DM, S_LEN / 2, 2, DM * 4, DM * 2, 64, 64, 1);
    encode(fn, &p.tm[TM_ATTN_A], attn, DM, S_LEN, 1, DM * 2, S_LEN * DM * 2, 64, 128, 1);
    encode(fn, &p.tm[TM_H_A], d_out, DM, S_LEN, 1, DM * 2, S_LEN * DM * 2, 64, 128, 1);
    encode(fn, &p.tm[TM_ACT_A], act, DF, S_LEN, 1, DF * 2, S_LEN * DF * 2, 64, 128, 1);
    encode(fn, &p.tm[TM_OUT16], d_out, DM, S_LEN, 1, DM * 2, S_LEN * DM * 2, 64, 16, 1);
    encode(fn, &p.tm[TM_OUT_ST], d_out, DM, S_LEN, 1, DM * 2, S_LEN * DM * 2, 64, 64, 1);
    encode(fn, &p.tm[TM_ACT_ST], act, DF, S_LEN, 1, DF * 2, S_LEN * DF * 2, 64, 64, 1);
    encode(fn, &p.tm[TM_WQKV], d_in[1], DM, DM, 3, 3 * DM * 2, DM * 2, 64, 32, 3);
    encode(fn, &p.tm[TM_WO], p.wo, 64, DM, DM / 64, DM * 2, 128, 64, 64, 2);
    encode(fn, &p.tm[TM_WG], d_in[4], 64, DM, DF / 64, DF * 2, 128, 64, 64, 2);
    encode(fn, &p.tm[TM_WU], d_in[5], 64, DM, DF / 64, DF * 2, 128, 64, 64, 2);
    encode(fn, &p.tm[TM_WD], d_in[6], 64, DF, DM / 64, DM * 2, 128, 64, 64, 2);
    cudaFuncSetAttribute(fused_block_kernel, cudaFuncAttributeMaxDynamicSharedMemorySize, SMEM_BYTES);
    p.ncta = 2 * build_schedule(p.sched);
  }
  fused_block_kernel<<<p.ncta, 384, SMEM_BYTES>>>(p);
}
```

```cpp
#include <cuda_runtime.h>
#include <cuda_bf16.h>
#include <cuda.h>
#include <stdint.h>
#include <string.h>

template <int N>
__device__ __forceinline__ void wgmma128(float (&d)[N], uint64_t da, uint64_t db) {
  asm volatile("wgmma.mma_async.sync.aligned.m64n128k16.f32.bf16.bf16 "
    "{%0, %1, %2, %3, %4, %5, %6, %7, %8, %9, %10, %11, %12, %13, %14, %15, %16, %17, %18, %19, %20, %21, %22, %23, %24, %25, %26, %27, %28, %29, %30, %31, %32, %33, %34, %35, %36, %37, %38, %39, %40, %41, %42, %43, %44, %45, %46, %47, %48, %49, %50, %51, %52, %53, %54, %55, %56, %57, %58, %59, %60, %61, %62, %63}, %64, %65, 1, 1, 1, 0, 1;"
    : "+f"(d[0]), "+f"(d[1]), "+f"(d[2]), "+f"(d[3]), "+f"(d[4]), "+f"(d[5]), "+f"(d[6]), "+f"(d[7]), "+f"(d[8]), "+f"(d[9]), "+f"(d[10]), "+f"(d[11]), "+f"(d[12]), "+f"(d[13]), "+f"(d[14]), "+f"(d[15]), "+f"(d[16]), "+f"(d[17]), "+f"(d[18]), "+f"(d[19]), "+f"(d[20]), "+f"(d[21]), "+f"(d[22]), "+f"(d[23]), "+f"(d[24]), "+f"(d[25]), "+f"(d[26]), "+f"(d[27]), "+f"(d[28]), "+f"(d[29]), "+f"(d[30]), "+f"(d[31]), "+f"(d[32]), "+f"(d[33]), "+f"(d[34]), "+f"(d[35]), "+f"(d[36]), "+f"(d[37]), "+f"(d[38]), "+f"(d[39]), "+f"(d[40]), "+f"(d[41]), "+f"(d[42]), "+f"(d[43]), "+f"(d[44]), "+f"(d[45]), "+f"(d[46]), "+f"(d[47]), "+f"(d[48]), "+f"(d[49]), "+f"(d[50]), "+f"(d[51]), "+f"(d[52]), "+f"(d[53]), "+f"(d[54]), "+f"(d[55]), "+f"(d[56]), "+f"(d[57]), "+f"(d[58]), "+f"(d[59]), "+f"(d[60]), "+f"(d[61]), "+f"(d[62]), "+f"(d[63])
    : "l"(da), "l"(db));
}
__device__ __forceinline__ void wgmma192(float (&d)[128], uint64_t da, uint64_t db) {
  asm volatile("wgmma.mma_async.sync.aligned.m64n192k16.f32.bf16.bf16 "
    "{%0, %1, %2, %3, %4, %5, %6, %7, %8, %9, %10, %11, %12, %13, %14, %15, %16, %17, %18, %19, %20, %21, %22, %23, %24, %25, %26, %27, %28, %29, %30, %31, %32, %33, %34, %35, %36, %37, %38, %39, %40, %41, %42, %43, %44, %45, %46, %47, %48, %49, %50, %51, %52, %53, %54, %55, %56, %57, %58, %59, %60, %61, %62, %63, %64, %65, %66, %67, %68, %69, %70, %71, %72, %73, %74, %75, %76, %77, %78, %79, %80, %81, %82, %83, %84, %85, %86, %87, %88, %89, %90, %91, %92, %93, %94, %95}, %96, %97, 1, 1, 1, 0, 1;"
    : "+f"(d[0]), "+f"(d[1]), "+f"(d[2]), "+f"(d[3]), "+f"(d[4]), "+f"(d[5]), "+f"(d[6]), "+f"(d[7]), "+f"(d[8]), "+f"(d[9]), "+f"(d[10]), "+f"(d[11]), "+f"(d[12]), "+f"(d[13]), "+f"(d[14]), "+f"(d[15]), "+f"(d[16]), "+f"(d[17]), "+f"(d[18]), "+f"(d[19]), "+f"(d[20]), "+f"(d[21]), "+f"(d[22]), "+f"(d[23]), "+f"(d[24]), "+f"(d[25]), "+f"(d[26]), "+f"(d[27]), "+f"(d[28]), "+f"(d[29]), "+f"(d[30]), "+f"(d[31]), "+f"(d[32]), "+f"(d[33]), "+f"(d[34]), "+f"(d[35]), "+f"(d[36]), "+f"(d[37]), "+f"(d[38]), "+f"(d[39]), "+f"(d[40]), "+f"(d[41]), "+f"(d[42]), "+f"(d[43]), "+f"(d[44]), "+f"(d[45]), "+f"(d[46]), "+f"(d[47]), "+f"(d[48]), "+f"(d[49]), "+f"(d[50]), "+f"(d[51]), "+f"(d[52]), "+f"(d[53]), "+f"(d[54]), "+f"(d[55]), "+f"(d[56]), "+f"(d[57]), "+f"(d[58]), "+f"(d[59]), "+f"(d[60]), "+f"(d[61]), "+f"(d[62]), "+f"(d[63]), "+f"(d[64]), "+f"(d[65]), "+f"(d[66]), "+f"(d[67]), "+f"(d[68]), "+f"(d[69]), "+f"(d[70]), "+f"(d[71]), "+f"(d[72]), "+f"(d[73]), "+f"(d[74]), "+f"(d[75]), "+f"(d[76]), "+f"(d[77]), "+f"(d[78]), "+f"(d[79]), "+f"(d[80]), "+f"(d[81]), "+f"(d[82]), "+f"(d[83]), "+f"(d[84]), "+f"(d[85]), "+f"(d[86]), "+f"(d[87]), "+f"(d[88]), "+f"(d[89]), "+f"(d[90]), "+f"(d[91]), "+f"(d[92]), "+f"(d[93]), "+f"(d[94]), "+f"(d[95])
    : "l"(da), "l"(db));
}
__device__ __forceinline__ void wgmma192_init(float (&d)[128], uint64_t da, uint64_t db) {
  asm volatile("wgmma.mma_async.sync.aligned.m64n192k16.f32.bf16.bf16 "
    "{%0, %1, %2, %3, %4, %5, %6, %7, %8, %9, %10, %11, %12, %13, %14, %15, %16, %17, %18, %19, %20, %21, %22, %23, %24, %25, %26, %27, %28, %29, %30, %31, %32, %33, %34, %35, %36, %37, %38, %39, %40, %41, %42, %43, %44, %45, %46, %47, %48, %49, %50, %51, %52, %53, %54, %55, %56, %57, %58, %59, %60, %61, %62, %63, %64, %65, %66, %67, %68, %69, %70, %71, %72, %73, %74, %75, %76, %77, %78, %79, %80, %81, %82, %83, %84, %85, %86, %87, %88, %89, %90, %91, %92, %93, %94, %95}, %96, %97, 0, 1, 1, 0, 1;"
    : "=f"(d[0]), "=f"(d[1]), "=f"(d[2]), "=f"(d[3]), "=f"(d[4]), "=f"(d[5]), "=f"(d[6]), "=f"(d[7]), "=f"(d[8]), "=f"(d[9]), "=f"(d[10]), "=f"(d[11]), "=f"(d[12]), "=f"(d[13]), "=f"(d[14]), "=f"(d[15]), "=f"(d[16]), "=f"(d[17]), "=f"(d[18]), "=f"(d[19]), "=f"(d[20]), "=f"(d[21]), "=f"(d[22]), "=f"(d[23]), "=f"(d[24]), "=f"(d[25]), "=f"(d[26]), "=f"(d[27]), "=f"(d[28]), "=f"(d[29]), "=f"(d[30]), "=f"(d[31]), "=f"(d[32]), "=f"(d[33]), "=f"(d[34]), "=f"(d[35]), "=f"(d[36]), "=f"(d[37]), "=f"(d[38]), "=f"(d[39]), "=f"(d[40]), "=f"(d[41]), "=f"(d[42]), "=f"(d[43]), "=f"(d[44]), "=f"(d[45]), "=f"(d[46]), "=f"(d[47]), "=f"(d[48]), "=f"(d[49]), "=f"(d[50]), "=f"(d[51]), "=f"(d[52]), "=f"(d[53]), "=f"(d[54]), "=f"(d[55]), "=f"(d[56]), "=f"(d[57]), "=f"(d[58]), "=f"(d[59]), "=f"(d[60]), "=f"(d[61]), "=f"(d[62]), "=f"(d[63]), "=f"(d[64]), "=f"(d[65]), "=f"(d[66]), "=f"(d[67]), "=f"(d[68]), "=f"(d[69]), "=f"(d[70]), "=f"(d[71]), "=f"(d[72]), "=f"(d[73]), "=f"(d[74]), "=f"(d[75]), "=f"(d[76]), "=f"(d[77]), "=f"(d[78]), "=f"(d[79]), "=f"(d[80]), "=f"(d[81]), "=f"(d[82]), "=f"(d[83]), "=f"(d[84]), "=f"(d[85]), "=f"(d[86]), "=f"(d[87]), "=f"(d[88]), "=f"(d[89]), "=f"(d[90]), "=f"(d[91]), "=f"(d[92]), "=f"(d[93]), "=f"(d[94]), "=f"(d[95])
    : "l"(da), "l"(db));
}
__device__ __forceinline__ void wgmma192_rs(float (&d)[128], uint32_t a0, uint32_t a1, uint32_t a2, uint32_t a3, uint64_t db) {
  asm volatile("wgmma.mma_async.sync.aligned.m64n192k16.f32.bf16.bf16 "
    "{%0, %1, %2, %3, %4, %5, %6, %7, %8, %9, %10, %11, %12, %13, %14, %15, %16, %17, %18, %19, %20, %21, %22, %23, %24, %25, %26, %27, %28, %29, %30, %31, %32, %33, %34, %35, %36, %37, %38, %39, %40, %41, %42, %43, %44, %45, %46, %47, %48, %49, %50, %51, %52, %53, %54, %55, %56, %57, %58, %59, %60, %61, %62, %63, %64, %65, %66, %67, %68, %69, %70, %71, %72, %73, %74, %75, %76, %77, %78, %79, %80, %81, %82, %83, %84, %85, %86, %87, %88, %89, %90, %91, %92, %93, %94, %95}, {%96, %97, %98, %99}, %100, 1, 1, 1, 1;"
    : "+f"(d[0]), "+f"(d[1]), "+f"(d[2]), "+f"(d[3]), "+f"(d[4]), "+f"(d[5]), "+f"(d[6]), "+f"(d[7]), "+f"(d[8]), "+f"(d[9]), "+f"(d[10]), "+f"(d[11]), "+f"(d[12]), "+f"(d[13]), "+f"(d[14]), "+f"(d[15]), "+f"(d[16]), "+f"(d[17]), "+f"(d[18]), "+f"(d[19]), "+f"(d[20]), "+f"(d[21]), "+f"(d[22]), "+f"(d[23]), "+f"(d[24]), "+f"(d[25]), "+f"(d[26]), "+f"(d[27]), "+f"(d[28]), "+f"(d[29]), "+f"(d[30]), "+f"(d[31]), "+f"(d[32]), "+f"(d[33]), "+f"(d[34]), "+f"(d[35]), "+f"(d[36]), "+f"(d[37]), "+f"(d[38]), "+f"(d[39]), "+f"(d[40]), "+f"(d[41]), "+f"(d[42]), "+f"(d[43]), "+f"(d[44]), "+f"(d[45]), "+f"(d[46]), "+f"(d[47]), "+f"(d[48]), "+f"(d[49]), "+f"(d[50]), "+f"(d[51]), "+f"(d[52]), "+f"(d[53]), "+f"(d[54]), "+f"(d[55]), "+f"(d[56]), "+f"(d[57]), "+f"(d[58]), "+f"(d[59]), "+f"(d[60]), "+f"(d[61]), "+f"(d[62]), "+f"(d[63]), "+f"(d[64]), "+f"(d[65]), "+f"(d[66]), "+f"(d[67]), "+f"(d[68]), "+f"(d[69]), "+f"(d[70]), "+f"(d[71]), "+f"(d[72]), "+f"(d[73]), "+f"(d[74]), "+f"(d[75]), "+f"(d[76]), "+f"(d[77]), "+f"(d[78]), "+f"(d[79]), "+f"(d[80]), "+f"(d[81]), "+f"(d[82]), "+f"(d[83]), "+f"(d[84]), "+f"(d[85]), "+f"(d[86]), "+f"(d[87]), "+f"(d[88]), "+f"(d[89]), "+f"(d[90]), "+f"(d[91]), "+f"(d[92]), "+f"(d[93]), "+f"(d[94]), "+f"(d[95])
    : "r"(a0), "r"(a1), "r"(a2), "r"(a3), "l"(db));
}

__device__ __forceinline__ void wgmma256(float (&d)[128], uint64_t da, uint64_t db) {
  asm volatile("wgmma.mma_async.sync.aligned.m64n256k16.f32.bf16.bf16 "
    "{%0, %1, %2, %3, %4, %5, %6, %7, %8, %9, %10, %11, %12, %13, %14, %15, %16, %17, %18, %19, %20, %21, %22, %23, %24, %25, %26, %27, %28, %29, %30, %31, %32, %33, %34, %35, %36, %37, %38, %39, %40, %41, %42, %43, %44, %45, %46, %47, %48, %49, %50, %51, %52, %53, %54, %55, %56, %57, %58, %59, %60, %61, %62, %63, %64, %65, %66, %67, %68, %69, %70, %71, %72, %73, %74, %75, %76, %77, %78, %79, %80, %81, %82, %83, %84, %85, %86, %87, %88, %89, %90, %91, %92, %93, %94, %95, %96, %97, %98, %99, %100, %101, %102, %103, %104, %105, %106, %107, %108, %109, %110, %111, %112, %113, %114, %115, %116, %117, %118, %119, %120, %121, %122, %123, %124, %125, %126, %127}, %128, %129, 1, 1, 1, 0, 1;"
    : "+f"(d[0]), "+f"(d[1]), "+f"(d[2]), "+f"(d[3]), "+f"(d[4]), "+f"(d[5]), "+f"(d[6]), "+f"(d[7]), "+f"(d[8]), "+f"(d[9]), "+f"(d[10]), "+f"(d[11]), "+f"(d[12]), "+f"(d[13]), "+f"(d[14]), "+f"(d[15]), "+f"(d[16]), "+f"(d[17]), "+f"(d[18]), "+f"(d[19]), "+f"(d[20]), "+f"(d[21]), "+f"(d[22]), "+f"(d[23]), "+f"(d[24]), "+f"(d[25]), "+f"(d[26]), "+f"(d[27]), "+f"(d[28]), "+f"(d[29]), "+f"(d[30]), "+f"(d[31]), "+f"(d[32]), "+f"(d[33]), "+f"(d[34]), "+f"(d[35]), "+f"(d[36]), "+f"(d[37]), "+f"(d[38]), "+f"(d[39]), "+f"(d[40]), "+f"(d[41]), "+f"(d[42]), "+f"(d[43]), "+f"(d[44]), "+f"(d[45]), "+f"(d[46]), "+f"(d[47]), "+f"(d[48]), "+f"(d[49]), "+f"(d[50]), "+f"(d[51]), "+f"(d[52]), "+f"(d[53]), "+f"(d[54]), "+f"(d[55]), "+f"(d[56]), "+f"(d[57]), "+f"(d[58]), "+f"(d[59]), "+f"(d[60]), "+f"(d[61]), "+f"(d[62]), "+f"(d[63]), "+f"(d[64]), "+f"(d[65]), "+f"(d[66]), "+f"(d[67]), "+f"(d[68]), "+f"(d[69]), "+f"(d[70]), "+f"(d[71]), "+f"(d[72]), "+f"(d[73]), "+f"(d[74]), "+f"(d[75]), "+f"(d[76]), "+f"(d[77]), "+f"(d[78]), "+f"(d[79]), "+f"(d[80]), "+f"(d[81]), "+f"(d[82]), "+f"(d[83]), "+f"(d[84]), "+f"(d[85]), "+f"(d[86]), "+f"(d[87]), "+f"(d[88]), "+f"(d[89]), "+f"(d[90]), "+f"(d[91]), "+f"(d[92]), "+f"(d[93]), "+f"(d[94]), "+f"(d[95]), "+f"(d[96]), "+f"(d[97]), "+f"(d[98]), "+f"(d[99]), "+f"(d[100]), "+f"(d[101]), "+f"(d[102]), "+f"(d[103]), "+f"(d[104]), "+f"(d[105]), "+f"(d[106]), "+f"(d[107]), "+f"(d[108]), "+f"(d[109]), "+f"(d[110]), "+f"(d[111]), "+f"(d[112]), "+f"(d[113]), "+f"(d[114]), "+f"(d[115]), "+f"(d[116]), "+f"(d[117]), "+f"(d[118]), "+f"(d[119]), "+f"(d[120]), "+f"(d[121]), "+f"(d[122]), "+f"(d[123]), "+f"(d[124]), "+f"(d[125]), "+f"(d[126]), "+f"(d[127])
    : "l"(da), "l"(db));
}
__device__ __forceinline__ void wgmma256_init(float (&d)[128], uint64_t da, uint64_t db) {
  asm volatile("wgmma.mma_async.sync.aligned.m64n256k16.f32.bf16.bf16 "
    "{%0, %1, %2, %3, %4, %5, %6, %7, %8, %9, %10, %11, %12, %13, %14, %15, %16, %17, %18, %19, %20, %21, %22, %23, %24, %25, %26, %27, %28, %29, %30, %31, %32, %33, %34, %35, %36, %37, %38, %39, %40, %41, %42, %43, %44, %45, %46, %47, %48, %49, %50, %51, %52, %53, %54, %55, %56, %57, %58, %59, %60, %61, %62, %63, %64, %65, %66, %67, %68, %69, %70, %71, %72, %73, %74, %75, %76, %77, %78, %79, %80, %81, %82, %83, %84, %85, %86, %87, %88, %89, %90, %91, %92, %93, %94, %95, %96, %97, %98, %99, %100, %101, %102, %103, %104, %105, %106, %107, %108, %109, %110, %111, %112, %113, %114, %115, %116, %117, %118, %119, %120, %121, %122, %123, %124, %125, %126, %127}, %128, %129, 0, 1, 1, 0, 1;"
    : "=f"(d[0]), "=f"(d[1]), "=f"(d[2]), "=f"(d[3]), "=f"(d[4]), "=f"(d[5]), "=f"(d[6]), "=f"(d[7]), "=f"(d[8]), "=f"(d[9]), "=f"(d[10]), "=f"(d[11]), "=f"(d[12]), "=f"(d[13]), "=f"(d[14]), "=f"(d[15]), "=f"(d[16]), "=f"(d[17]), "=f"(d[18]), "=f"(d[19]), "=f"(d[20]), "=f"(d[21]), "=f"(d[22]), "=f"(d[23]), "=f"(d[24]), "=f"(d[25]), "=f"(d[26]), "=f"(d[27]), "=f"(d[28]), "=f"(d[29]), "=f"(d[30]), "=f"(d[31]), "=f"(d[32]), "=f"(d[33]), "=f"(d[34]), "=f"(d[35]), "=f"(d[36]), "=f"(d[37]), "=f"(d[38]), "=f"(d[39]), "=f"(d[40]), "=f"(d[41]), "=f"(d[42]), "=f"(d[43]), "=f"(d[44]), "=f"(d[45]), "=f"(d[46]), "=f"(d[47]), "=f"(d[48]), "=f"(d[49]), "=f"(d[50]), "=f"(d[51]), "=f"(d[52]), "=f"(d[53]), "=f"(d[54]), "=f"(d[55]), "=f"(d[56]), "=f"(d[57]), "=f"(d[58]), "=f"(d[59]), "=f"(d[60]), "=f"(d[61]), "=f"(d[62]), "=f"(d[63]), "=f"(d[64]), "=f"(d[65]), "=f"(d[66]), "=f"(d[67]), "=f"(d[68]), "=f"(d[69]), "=f"(d[70]), "=f"(d[71]), "=f"(d[72]), "=f"(d[73]), "=f"(d[74]), "=f"(d[75]), "=f"(d[76]), "=f"(d[77]), "=f"(d[78]), "=f"(d[79]), "=f"(d[80]), "=f"(d[81]), "=f"(d[82]), "=f"(d[83]), "=f"(d[84]), "=f"(d[85]), "=f"(d[86]), "=f"(d[87]), "=f"(d[88]), "=f"(d[89]), "=f"(d[90]), "=f"(d[91]), "=f"(d[92]), "=f"(d[93]), "=f"(d[94]), "=f"(d[95]), "=f"(d[96]), "=f"(d[97]), "=f"(d[98]), "=f"(d[99]), "=f"(d[100]), "=f"(d[101]), "=f"(d[102]), "=f"(d[103]), "=f"(d[104]), "=f"(d[105]), "=f"(d[106]), "=f"(d[107]), "=f"(d[108]), "=f"(d[109]), "=f"(d[110]), "=f"(d[111]), "=f"(d[112]), "=f"(d[113]), "=f"(d[114]), "=f"(d[115]), "=f"(d[116]), "=f"(d[117]), "=f"(d[118]), "=f"(d[119]), "=f"(d[120]), "=f"(d[121]), "=f"(d[122]), "=f"(d[123]), "=f"(d[124]), "=f"(d[125]), "=f"(d[126]), "=f"(d[127])
    : "l"(da), "l"(db));
}

namespace {

constexpr int S_LEN = 2048, DM = 1024, DF = 3584;
constexpr int MAXT = 16;
constexpr int MAXPAIRS = 66;
constexpr uint32_t TILE_END = 0xFFFFFFFFu;
constexpr int FLAG_SLEEP = 100;
constexpr int X_STEP = 5;
constexpr int DEF_A = 7, DEF_AW = 5, DEF_G = 8, DEF_R = 4;
constexpr int TAIL = 3;

__device__ __forceinline__ int t_type(uint32_t t) { return t & 3; }
__device__ __forceinline__ int t_mp(uint32_t t) { return (t >> 2) & 7; }
__device__ __forceinline__ int t_idx(uint32_t t) { return (t >> 5) & 31; }
__device__ __forceinline__ int t_k0(uint32_t t) { return (t >> 10) & 63; }
__device__ __forceinline__ int t_nk(uint32_t t) { return (t >> 16) & 63; }
__device__ __forceinline__ int t_sh(uint32_t t) { return (t >> 1) & 1; }
__device__ __forceinline__ int t_deps(uint32_t t, int n) { return ((t_k0(t) + n - 1) >> t_sh(t)) - (t_k0(t) >> t_sh(t)) + 1; }
__device__ __forceinline__ int p1_k(int mp, int k) { return (k + ((mp & 2) << 2)) & 15; }

enum { TM_X1, TM_WQKV, TM_ATTN_ST, TM_ATTN_A, TM_H_A, TM_ACT_A, TM_OUT_ST, TM_OUT16, TM_ACT_ST, TM_WO, TM_WG, TM_WU, TM_WD, TM_COUNT };

struct alignas(64) Params {
  CUtensorMap tm[TM_COUNT];
  const __nv_bfloat16* x;
  const __nv_bfloat16* wo;
  __nv_bfloat16* out;
  int ncta;
  uint32_t sched[MAXPAIRS * MAXT];
};

__device__ __align__(128) __nv_bfloat16 g_attn[S_LEN * DM];
__device__ __align__(128) __nv_bfloat16 g_act[S_LEN * DF];
__device__ __align__(64) uint2 g_xst[S_LEN + 8];
__device__ __align__(128) uint32_t g_csp[16 * 8 * 192];
__device__ __align__(128) uint2 g_rm[DM];
__device__ __align__(128) uint32_t g_pdot[16 * S_LEN];
__device__ __align__(128) uint2 g_hmean[S_LEN / 2];
__device__ __align__(128) uint32_t g_hrs[S_LEN];
__device__ __align__(128) uint4 g_halo[16 * 16 * 128];
constexpr int FL_LAUNCH = 0, FL_COPY = 32, FL_OUT = 96, FL_COUNT = FL_OUT + 24 * 32;
__device__ __align__(128) uint32_t g_flags[FL_COUNT];

constexpr int NSTAGE = 4;
constexpr uint32_t STAGE_BYTES = 49152, A_BYTES = 16384;
constexpr uint32_t OFF_STG = NSTAGE * STAGE_BYTES;
constexpr uint32_t OFF_BAR = OFF_STG + 32768;
constexpr uint32_t B_FULL = OFF_BAR, B_EMPTY = OFF_BAR + 32, B_OUTF = OFF_BAR + 64, B_OUTE = OFF_BAR + 96, B_ROW = OFF_BAR + 128,
                   B_HALO = OFF_BAR + 176, B_RM = OFF_BAR + 192, B_EPOCH = OFF_BAR + 200, B_CS = OFF_BAR + 208,
                   B_ROWDONE = OFF_BAR + 216, B_GATE = OFF_BAR + 224, B_COPY = OFF_BAR + 232, B_DUMP = OFF_BAR + 168;
constexpr uint32_t B_HALF = OFF_BAR + 240, B_GO = OFF_BAR + 248, B_DUTY = OFF_BAR + 264;
constexpr uint32_t OFF_MISC = OFF_BAR + 272;
constexpr uint32_t M_EPOCH = OFF_MISC, M_DEP = OFF_MISC + 8, M_PAD = OFF_MISC + 16, M_CS = OFF_MISC + 32, M_RM = M_CS + 768 + 96;
constexpr uint32_t SMEM_BYTES = M_RM + 256;

__device__ __forceinline__ void mbar_init(uint32_t bar, uint32_t cnt) { asm volatile("mbarrier.init.shared::cta.b64 [%0], %1;" :: "r"(bar), "r"(cnt)); }
__device__ __forceinline__ void mbar_arrive(uint32_t bar) { asm volatile("mbarrier.arrive.shared::cta.b64 _, [%0];" :: "r"(bar) : "memory"); }
__device__ __forceinline__ void mbar_arrive_warp(uint32_t bar) {
  __syncwarp();
  asm volatile("{\n.reg .pred p;\nelect.sync _|p, 0xffffffff;\n@p mbarrier.arrive.shared::cta.b64 _, [%0];\n}" :: "r"(bar) : "memory");
}
__device__ __forceinline__ uint32_t mapa(uint32_t addr, uint32_t cta) {
  uint32_t r; asm("mapa.shared::cluster.u32 %0, %1, %2;" : "=r"(r) : "r"(addr), "r"(cta)); return r;
}
__device__ __forceinline__ void mbar_arrive_remote(uint32_t cluster_addr) {
  asm volatile("mbarrier.arrive.shared::cluster.b64 _, [%0];" :: "r"(cluster_addr) : "memory");
}
__device__ __forceinline__ void mbar_wait(uint32_t bar, uint32_t parity) {
  asm volatile("{\n.reg .pred p;\nWAIT_LOOP:\n"
               "mbarrier.try_wait.parity.shared::cta.b64 p, [%0], %1, 5000;\n@!p bra WAIT_LOOP;\n}"
               :: "r"(bar), "r"(parity) : "memory");
}
__device__ __forceinline__ bool mbar_test(uint32_t bar, uint32_t parity) {
  uint32_t ok;
  asm volatile("{\n.reg .pred p;\nmbarrier.test_wait.parity.shared::cta.b64 p, [%1], %2;\nselp.u32 %0, 1, 0, p;\n}"
               : "=r"(ok) : "r"(bar), "r"(parity) : "memory");
  return __all_sync(0xffffffffu, ok != 0);
}
__device__ __forceinline__ void flag_add(uint32_t* flag, uint32_t n) {
  asm volatile("{\n.reg .pred p;\nfence.release.gpu;\nsetp.ne.u64 p, %0, 0;\n@p red.relaxed.gpu.global.add.u32 [%0], %1;\n}" :: "l"(flag), "r"(n) : "memory");
}
__device__ __forceinline__ void fence_async_all() { asm volatile("fence.proxy.async.global;" ::: "memory"); }
__device__ __forceinline__ void fence_async_smem() { asm volatile("fence.proxy.async.shared::cta;" ::: "memory"); }

__device__ __forceinline__ void tma_st3d(const CUtensorMap* m, uint32_t src, int c0, int c1, int c2) {
  asm volatile("{\n.reg .pred p;\nelect.sync _|p, 0xffffffff;\n"
               "@p cp.async.bulk.tensor.3d.global.shared::cta.bulk_group [%0, {%2, %3, %4}], [%1];\n}"
               :: "l"(m), "r"(src), "r"(c0), "r"(c1), "r"(c2) : "memory");
}
__device__ __forceinline__ void tma_add3d(const CUtensorMap* m, uint32_t src, int c0, int c1, int c2) {
  asm volatile("{\n.reg .pred p;\nelect.sync _|p, 0xffffffff;\n"
               "@p cp.reduce.async.bulk.tensor.3d.global.shared::cta.add.tile.bulk_group [%0, {%2, %3, %4}], [%1];\n}"
               :: "l"(m), "r"(src), "r"(c0), "r"(c1), "r"(c2) : "memory");
}
__device__ __forceinline__ void bulk_commit() { asm volatile("cp.async.bulk.commit_group;" ::: "memory"); }
template <int N> __device__ __forceinline__ void bulk_wait_read() { asm volatile("cp.async.bulk.wait_group.read %0;" :: "n"(N) : "memory"); }
__device__ __forceinline__ void bulk_wait_all() { asm volatile("cp.async.bulk.wait_group 0;" ::: "memory"); }

__device__ __forceinline__ void wg_fence() { asm volatile("wgmma.fence.sync.aligned;" ::: "memory"); }
__device__ __forceinline__ void wg_commit() { asm volatile("wgmma.commit_group.sync.aligned;" ::: "memory"); }
template <int N> __device__ __forceinline__ void wg_wait() { asm volatile("wgmma.wait_group.sync.aligned %0;" :: "n"(N) : "memory"); }
__device__ __forceinline__ uint64_t desc64(uint32_t lo) { return ((uint64_t)0x40000040u << 32) | lo; }

__device__ __forceinline__ uint32_t pack2(float lo, float hi) { uint32_t r; asm("cvt.rn.bf16x2.f32 %0, %1, %2;" : "=r"(r) : "f"(hi), "f"(lo)); return r; }
__device__ __forceinline__ float bf_lo(uint32_t v) { return __uint_as_float(v << 16); }
__device__ __forceinline__ float bf_hi(uint32_t v) { return __uint_as_float(v & 0xffff0000u); }
__device__ __forceinline__ uint32_t add2(uint32_t a, uint32_t b) { uint32_t r; asm("add.rn.bf16x2 %0, %1, %2;" : "=r"(r) : "r"(a), "r"(b)); return r; }
__device__ __forceinline__ uint32_t fma2(uint32_t a, uint32_t b, uint32_t c) { uint32_t r; asm("fma.rn.bf16x2 %0, %1, %2, %3;" : "=r"(r) : "r"(a), "r"(b), "r"(c)); return r; }
__device__ __forceinline__ uint32_t mul2(uint32_t a, uint32_t b) { uint32_t r; asm("mul.rn.bf16x2 %0, %1, %2;" : "=r"(r) : "r"(a), "r"(b)); return r; }
__device__ __forceinline__ float tanh_hw(float x) { float y; asm("tanh.approx.f32 %0, %1;" : "=f"(y) : "f"(x)); return y; }
__device__ __forceinline__ float ex2(float x) { float y; asm("ex2.approx.ftz.f32 %0, %1;" : "=f"(y) : "f"(x)); return y; }
__device__ __forceinline__ float rcp(float x) { float y; asm("rcp.approx.ftz.f32 %0, %1;" : "=f"(y) : "f"(x)); return y; }
__device__ __forceinline__ void stsm4(uint32_t addr, uint32_t a, uint32_t b, uint32_t c, uint32_t d) {
  asm volatile("stmatrix.sync.aligned.m8n8.x4.shared.b16 [%0], {%1, %2, %3, %4};" :: "r"(addr), "r"(a), "r"(b), "r"(c), "r"(d) : "memory");
}
__device__ __forceinline__ void stsm4t(uint32_t addr, uint32_t a, uint32_t b, uint32_t c, uint32_t d) {
  asm volatile("stmatrix.sync.aligned.m8n8.x4.trans.shared.b16 [%0], {%1, %2, %3, %4};" :: "r"(addr), "r"(a), "r"(b), "r"(c), "r"(d) : "memory");
}
__device__ __forceinline__ uint4 ld_gpu128(const uint4* p) {
  uint4 v;
  asm volatile("ld.relaxed.gpu.global.v4.u32 {%0, %1, %2, %3}, [%4];" : "=r"(v.x), "=r"(v.y), "=r"(v.z), "=r"(v.w) : "l"(p) : "memory");
  return v;
}
template <int OFF>
__device__ __forceinline__ uint2 ld_gpu64(const void* p) {
  uint2 v;
  asm volatile("ld.relaxed.gpu.global.v2.u32 {%0, %1}, [%2 + %3];" : "=r"(v.x), "=r"(v.y) : "l"(p), "n"(OFF) : "memory");
  return v;
}
__device__ __forceinline__ void st_gpu128_if(bool on, uint4* p, uint32_t a, uint32_t b, uint32_t c, uint32_t d) {
  asm volatile("{\n.reg .pred p;\nsetp.ne.u32 p, %5, 0;\n@p st.relaxed.gpu.global.v4.u32 [%0], {%1, %2, %3, %4};\n}"
               :: "l"(p), "r"(a), "r"(b), "r"(c), "r"(d), "r"((uint32_t)on) : "memory");
}
__device__ __forceinline__ void st_gpu64_if(bool on, uint2* p, uint32_t a, uint32_t b) {
  asm volatile("{\n.reg .pred p;\nsetp.ne.u32 p, %3, 0;\n@p st.relaxed.gpu.global.v2.u32 [%0], {%1, %2};\n}"
               :: "l"(p), "r"(a), "r"(b), "r"((uint32_t)on) : "memory");
}
template <int OFF>
__device__ __forceinline__ uint32_t ld_gpu32(const void* p) {
  uint32_t v;
  asm volatile("ld.relaxed.gpu.global.u32 %0, [%1 + %2];" : "=r"(v) : "l"(p), "n"(OFF) : "memory");
  return v;
}
__device__ __forceinline__ void st_gpu32_if(bool on, uint32_t* p, uint32_t a) {
  asm volatile("{\n.reg .pred p;\nsetp.ne.u32 p, %2, 0;\n@p st.relaxed.gpu.global.u32 [%0], %1;\n}" :: "l"(p), "r"(a), "r"((uint32_t)on) : "memory");
}
__device__ __forceinline__ uint32_t tagged(float v, uint32_t tag) { return __byte_perm(__float_as_uint(v), tag, 0x3214); }
__device__ __forceinline__ float untagged(uint32_t v) { return __uint_as_float(v & ~255u); }
__device__ __forceinline__ uint32_t lds32(uint32_t a) {
  uint32_t v;
  asm volatile("ld.shared.u32 %0, [%1];" : "=r"(v) : "r"(a) : "memory");
  return v;
}
__device__ __forceinline__ uint4 lds128(uint32_t a) {
  uint4 v;
  asm volatile("ld.shared.v4.u32 {%0, %1, %2, %3}, [%4];" : "=r"(v.x), "=r"(v.y), "=r"(v.z), "=r"(v.w) : "r"(a) : "memory");
  return v;
}
__device__ __forceinline__ void ldsm4(uint32_t addr, uint32_t& a, uint32_t& b, uint32_t& c, uint32_t& d) {
  asm volatile("ldmatrix.sync.aligned.m8n8.x4.shared.b16 {%0, %1, %2, %3}, [%4];" : "=r"(a), "=r"(b), "=r"(c), "=r"(d) : "r"(addr) : "memory");
}
__device__ __forceinline__ uint32_t movmat(uint32_t a) { uint32_t d; asm volatile("movmatrix.sync.aligned.m8n8.trans.b16 %0, %1;" : "=r"(d) : "r"(a)); return d; }
__device__ __forceinline__ void mma16(float (&d)[4], uint32_t a0, uint32_t a1, uint32_t a2, uint32_t a3, uint32_t b0, uint32_t b1) {
  asm volatile("mma.sync.aligned.m16n8k16.row.col.f32.bf16.bf16.f32 {%0, %1, %2, %3}, {%4, %5, %6, %7}, {%8, %9}, {%0, %1, %2, %3};"
               : "+f"(d[0]), "+f"(d[1]), "+f"(d[2]), "+f"(d[3]) : "r"(a0), "r"(a1), "r"(a2), "r"(a3), "r"(b0), "r"(b1));
}
__device__ __forceinline__ void mma16_init(float (&d)[4], uint32_t a0, uint32_t a1, uint32_t a2, uint32_t a3, uint32_t b0, uint32_t b1) {
  asm volatile("mma.sync.aligned.m16n8k16.row.col.f32.bf16.bf16.f32 {%0, %1, %2, %3}, {%4, %5, %6, %7}, {%8, %9}, {%10, %10, %10, %10};"
               : "=f"(d[0]), "=f"(d[1]), "=f"(d[2]), "=f"(d[3]) : "r"(a0), "r"(a1), "r"(a2), "r"(a3), "r"(b0), "r"(b1), "f"(0.f));
}
__device__ __forceinline__ float quad_sum(float v) { v += __shfl_xor_sync(0xffffffffu, v, 1); return v + __shfl_xor_sync(0xffffffffu, v, 2); }
__device__ __forceinline__ float quad_max(float v) { v = fmaxf(v, __shfl_xor_sync(0xffffffffu, v, 1)); return fmaxf(v, __shfl_xor_sync(0xffffffffu, v, 2)); }

__device__ __forceinline__ int fresh_tid() { int t; asm volatile("mov.u32 %0, %%tid.x;" : "=r"(t)); return t; }

__device__ __forceinline__ void mbar_spin(uint32_t bar, uint32_t parity) {
  asm volatile("{\n.reg .pred p;\nWAIT_LOOP:\nmbarrier.try_wait.parity.shared::cta.b64 p, [%0], %1;\n@!p bra WAIT_LOOP;\n}" :: "r"(bar), "r"(parity) : "memory");
}

struct Cons {
  uint32_t sb;
  uint32_t empty_r;
  uint32_t srow;
  int w, rank;
  uint32_t s, ph;
  uint32_t prev;
  uint32_t phb;
};

__device__ __forceinline__ void release_prev(Cons& c) {
  if (c.prev < NSTAGE && c.empty_r) mbar_arrive_remote(c.empty_r + 8 * c.prev);
}

template <int N, bool FIRST = false, bool WAIT = true>
__device__ __forceinline__ void mma_step(Cons& c, float (&acc)[128]) {
  if (WAIT) mbar_spin(c.sb + B_FULL + 8 * c.s, c.ph);
  const uint32_t st = ((c.sb & 0x3FFFF) >> 4) + c.s * (STAGE_BYTES >> 4);
  const uint32_t da = st + c.w * 512 + (1u << 16);
  const uint32_t db = st + (A_BYTES >> 4) + ((N == 192 ? 256u : 512u) << 16);
  wg_fence();
#pragma unroll
  for (int kk = 0; kk < 4; kk++) {
    const uint32_t bo = N == 192 ? (kk >> 1) * 768 + (kk & 1) * 128 : kk * 128;
    if (FIRST && kk == 0) {
      if (N == 192) wgmma192_init(acc, desc64(da), desc64(db));
      else wgmma256_init(acc, desc64(da), desc64(db));
    } else {
      if (N == 192) wgmma192(acc, desc64(da + kk * 2), desc64(db + bo));
      else wgmma256(acc, desc64(da + kk * 2), desc64(db + bo));
    }
    if (kk == 0) {
      wg_commit();
      wg_wait<1>();
      release_prev(c);
    }
  }
  wg_commit();
  c.prev = c.s;
  if (++c.s == NSTAGE) { c.s = 0; c.ph ^= 1; }
}

template <int CHUNK>
__device__ __forceinline__ uint32_t srow(const Cons& c) {
  if (CHUNK == 0) return c.srow;
  uint32_t r;
  asm volatile("xor.b32 %0, %1, %2;" : "=r"(r) : "r"(c.srow), "n"(CHUNK << 4));
  return r;
}
__device__ __forceinline__ void out_acquire(Cons& c, int sub) {
  mbar_spin(c.sb + B_OUTE + c.w * 16 + sub * 8, ((c.phb >> sub) & 1) ^ 1);
  c.phb ^= 1u << sub;
}
__device__ __forceinline__ void out_publish(const Cons& c, int sub) {
  fence_async_smem();
  mbar_arrive_warp(c.sb + B_OUTF + c.w * 16 + sub * 8);
}

__device__ __forceinline__ float asf(uint32_t v) { return __uint_as_float(v); }
__device__ __forceinline__ uint32_t asu(float v) { return __float_as_uint(v); }

__device__ __forceinline__ void sched_fence(uint32_t sb) {
  asm volatile("{\n.reg .pred p;\n.reg .u32 t;\nmov.u32 t, %%clock;\nsetp.eq.u32 p, t, 0;\n@p st.shared.u32 [%0], t;\n}" :: "r"(sb + M_PAD) : "memory");
}

template <int N, bool FIRST = false, bool WAIT = true>
__device__ __forceinline__ void next_step(Cons& c, float (&acc)[128]) {
  if (N) {
    if (!WAIT) {
      sched_fence(c.sb);
      asm volatile("bar.sync 3, 256;" ::: "memory");
    }
    mma_step<N, FIRST, WAIT>(c, acc);
    sched_fence(c.sb);
  }
}

__device__ __forceinline__ void p1_park(const Cons& c, const float (&acc)[128], uint32_t (&lo)[24], uint32_t (&hi)[24], int g, uint32_t tile) {
#pragma unroll
  for (int j = 8; j < 24; j++) hi[j] = pack2(acc[4 * j + 2], acc[4 * j + 3]);
  const int l = fresh_tid() & 31;
  if (g < 8) {
#pragma unroll
    for (int i = 0; i < 4; i++)
      stsm4(c.sb + OFF_STG + (g >> 2) * 16384 + (g & 3) * 2048 + l * 16 + i * 512, hi[8 + 4 * i], hi[9 + 4 * i], hi[10 + 4 * i], hi[11 + 4 * i]);
    mbar_arrive_warp(c.sb + B_HALO + (g >> 2) * 8);
  } else {
    uint4* box = g_halo + ((t_mp(tile) * 2 + c.rank) * 16 + t_idx(tile)) * 128 + l;
#pragma unroll
    for (int i = 0; i < 4; i++) st_gpu128_if(t_mp(tile) < 7, box + i * 32, ~hi[8 + 4 * i], ~hi[9 + 4 * i], ~hi[10 + 4 * i], ~hi[11 + 4 * i]);
  }
#pragma unroll
  for (int j = 0; j < 8; j++) hi[j] = pack2(acc[4 * j + 2], acc[4 * j + 3]);
#pragma unroll
  for (int j = 0; j < 24; j++) lo[j] = pack2(acc[4 * j], acc[4 * j + 1]);
}

__device__ __forceinline__ void p1_centre(const Cons& c, float (&acc)[128], float mu0, float mu1) {
  const uint32_t on = (fresh_tid() & 3) == 0 ? 0xffffffffu : 0u;
  const uint32_t h0 = pack2(-mu0, -mu0), h1 = pack2(-mu1, -mu1);
  const float r0 = -mu0 - bf_lo(h0), r1 = -mu1 - bf_lo(h1);
  const uint32_t a0 = h0 & on, a1 = h1 & on, a2 = pack2(r0, r0) & on, a3 = pack2(r1, r1) & on;
  wg_fence();
  wgmma192_rs(acc, a0, a1, a2, a3, ((uint64_t)2 << 32) | (((c.sb + M_CS) & 0x3FFFF) >> 4));
  wg_commit();
}

template <int DEFER>
__device__ __forceinline__ void p1_attention(Cons& c, float (&acc)[128], uint32_t (&lo)[24], uint32_t (&hi)[24], const float (&ev)[8], uint32_t tile) {
  next_step<DEFER, true>(c, acc);
  if (DEFER < 256) next_step<DEFER>(c, acc);
  const int tw = fresh_tid() & 127, l = tw & 31, q = l & 3, r = l >> 2;
  const uint32_t mine = c.sb + OFF_STG + c.w * 16384 + (tw >> 5) * 2048 + l * 16;
#pragma unroll
  for (int j = 16; j < 24; j++) { lo[j] = movmat(lo[j]); hi[j] = movmat(hi[j]); }
  const bool c0 = 2 * q <= r, c1 = 2 * q + 1 <= r;
  constexpr float QS = 0.17677669529663687f * 1.4426950408889634f;
  const float kl0 = c0 ? ev[4] : ev[2], kl1 = c1 ? ev[5] : ev[3], ql0 = ev[0] * QS * kl0, ql1 = ev[0] * QS * kl1;
  const float kh0 = c0 ? ev[6] : ev[4], kh1 = c1 ? ev[7] : ev[5], qh0 = ev[1] * QS * kh0, qh1 = ev[1] * QS * kh1;
  next_step<DEFER>(c, acc);
  mbar_spin(c.sb + B_HALO + c.w * 8, (c.phb >> 2) & 1);
  c.phb ^= 4;
  float sp[2][4], s0[2][4], s1[2][4];
  {
    uint32_t kp[8];
    ldsm4(mine, kp[0], kp[1], kp[2], kp[3]);
    ldsm4(mine + 512, kp[4], kp[5], kp[6], kp[7]);
    if (DEFER) { mbar_spin(c.sb + B_FULL + 8 * c.s, c.ph); sched_fence(c.sb); }
#pragma unroll
    for (int h = 0; h < 2; h++) {
      const int a = 4 * h, b = a + 2;
      mma16_init(s0[h], lo[a], hi[a], lo[a + 1], hi[a + 1], lo[8 + a], lo[9 + a]);
      mma16_init(s1[h], lo[a], hi[a], lo[a + 1], hi[a + 1], hi[8 + a], hi[9 + a]);
      mma16_init(sp[h], lo[a], hi[a], lo[a + 1], hi[a + 1], kp[a], kp[a + 1]);
      mma16(s0[h], lo[b], hi[b], lo[b + 1], hi[b + 1], lo[8 + b], lo[9 + b]);
      mma16(s1[h], lo[b], hi[b], lo[b + 1], hi[b + 1], hi[8 + b], hi[9 + b]);
      mma16(sp[h], lo[b], hi[b], lo[b + 1], hi[b + 1], kp[b], kp[b + 1]);
    }
  }
  next_step<DEFER, false, false>(c, acc);
  float x[4][2];
  {
    const bool first = (t_mp(tile) | c.w | (tw >> 5)) == 0;
#pragma unroll
    for (int h = 0; h < 2; h++) {
      x[h][0] = first && !c0 ? -INFINITY : (c0 ? s0[h][0] : sp[h][0]) * ql0;
      x[h][1] = first && !c1 ? -INFINITY : (c1 ? s0[h][1] : sp[h][1]) * ql1;
      x[2 + h][0] = (c0 ? s1[h][2] : s0[h][2]) * qh0;
      x[2 + h][1] = (c1 ? s1[h][3] : s0[h][3]) * qh1;
    }
#pragma unroll
    for (int i = 0; i < 4; i++) {
      const float m = quad_max(fmaxf(x[i][0], x[i][1]));
      x[i][0] = ex2(x[i][0] - m); x[i][1] = ex2(x[i][1] - m);
    }
  }
  if (DEFER < 256) next_step<DEFER>(c, acc);
  float ol[4][4], oh[4][4];
  {
    uint32_t vp[4][4], pb[4][2];
#pragma unroll
    for (int m = 0; m < 4; m++) {
      asm volatile("ldmatrix.sync.aligned.m8n8.x2.trans.shared.b16 {%0, %1}, [%2];" : "=r"(vp[m][0]), "=r"(vp[m][1]) : "r"(mine + 1024 + m * 256) : "memory");
      asm volatile("xor.b32 %0, %2, %4;\nxor.b32 %1, %3, %4;" : "=r"(vp[m][2]), "=r"(vp[m][3]) : "r"(lo[16 + 2 * m]), "r"(lo[17 + 2 * m]), "r"(c.sb & 1));
    }
    const uint32_t cur = (c0 ? 0x0000ffffu : 0u) | (c1 ? 0xffff0000u : 0u);
#pragma unroll
    for (int i = 0; i < 4; i++) {
      const float inv = rcp(quad_sum(x[i][0] + x[i][1]));
      const uint32_t pr = pack2(x[i][0] * inv * (i < 2 ? kl0 : kh0), x[i][1] * inv * (i < 2 ? kl1 : kh1));
      pb[i][0] = pr & ~cur; pb[i][1] = pr & cur;
    }
    if (DEFER) { mbar_spin(c.sb + B_FULL + 8 * c.s, c.ph); sched_fence(c.sb); }
#pragma unroll
    for (int m = 0; m < 4; m++) {
      mma16_init(oh[m], lo[16 + 2 * m], lo[17 + 2 * m], hi[16 + 2 * m], hi[17 + 2 * m], pb[2 + (m >> 1)][0], pb[2 + (m >> 1)][1]);
      mma16_init(ol[m], vp[m][0], vp[m][1], vp[m][2], vp[m][3], pb[m >> 1][0], pb[m >> 1][1]);
    }
  }
  next_step<DEFER, false, false>(c, acc);
#pragma unroll
  for (int m = 0; m < 4; m++)
    stsm4t(c.srow ^ (m << 5), pack2(ol[m][0], ol[m][1]), pack2(oh[m][0], oh[m][1]), pack2(ol[m][2], ol[m][3]), pack2(oh[m][2], oh[m][3]));
  next_step<DEFER>(c, acc);
  out_publish(c, 0);
  mbar_spin(c.sb + B_RM, 0);
  float d[4] = {0.f, 0.f, 0.f, 0.f};
#pragma unroll
  for (int m = 0; m < 4; m += 2) {
    const uint4 rm = lds128(c.sb + M_RM + m * 64 + r * 16);
    d[0] = fmaf(ol[m][0], asf(rm.x), fmaf(ol[m][2], asf(rm.y), fmaf(ol[m + 1][0], asf(rm.z), fmaf(ol[m + 1][2], asf(rm.w), d[0]))));
    d[1] = fmaf(ol[m][1], asf(rm.x), fmaf(ol[m][3], asf(rm.y), fmaf(ol[m + 1][1], asf(rm.z), fmaf(ol[m + 1][3], asf(rm.w), d[1]))));
    d[2] = fmaf(oh[m][0], asf(rm.x), fmaf(oh[m][2], asf(rm.y), fmaf(oh[m + 1][0], asf(rm.z), fmaf(oh[m + 1][2], asf(rm.w), d[2]))));
    d[3] = fmaf(oh[m][1], asf(rm.x), fmaf(oh[m][3], asf(rm.y), fmaf(oh[m + 1][1], asf(rm.z), fmaf(oh[m + 1][3], asf(rm.w), d[3]))));
  }
  const bool up = l & 16, odd = l & 8;
  const float e0 = (up ? d[2] : d[0]) + __shfl_xor_sync(0xffffffffu, up ? d[0] : d[2], 16);
  const float e1 = (up ? d[3] : d[1]) + __shfl_xor_sync(0xffffffffu, up ? d[1] : d[3], 16);
  float f = (odd ? e1 : e0) + __shfl_xor_sync(0xffffffffu, odd ? e0 : e1, 8);
  f += __shfl_xor_sync(0xffffffffu, f, 4);
  st_gpu32_if(!(l & 4),
              g_pdot + t_idx(tile) * S_LEN + c.rank * 1024 + t_mp(tile) * 128 + c.w * 64 + (tw >> 5) * 16 + (l >> 4) * 8 + 2 * q + ((l >> 3) & 1),
              tagged(f, lds32(c.sb + M_EPOCH)));
}

__device__ __forceinline__ void cs_accumulate(const Cons& c, uint32_t (&pk)[64], uint32_t off) {
#pragma unroll
  for (int g = 0; g < 3; g++) {
    uint32_t a, b;
    asm volatile("ld.shared.v2.b32 {%0, %1}, [%2];" : "=r"(a), "=r"(b) : "r"(off + c.prev * STAGE_BYTES + g * 4096) : "memory");
    pk[4 * g] = asu(asf(pk[4 * g]) + bf_lo(a)); pk[4 * g + 1] = asu(asf(pk[4 * g + 1]) + bf_hi(a));
    pk[4 * g + 2] = asu(asf(pk[4 * g + 2]) + bf_lo(b)); pk[4 * g + 3] = asu(asf(pk[4 * g + 3]) + bf_hi(b));
  }
}
__device__ __forceinline__ void cs_dump(const Cons& c, const uint32_t (&pk)[64]) {
  const int t = fresh_tid();
  const bool up = t & 16;
#pragma unroll
  for (int g = 0; g < 3; g++) {
    const float a = asf(up ? pk[4 * g + 2] : pk[4 * g]) + __shfl_xor_sync(0xffffffffu, asf(up ? pk[4 * g] : pk[4 * g + 2]), 16);
    const float b = asf(up ? pk[4 * g + 3] : pk[4 * g + 1]) + __shfl_xor_sync(0xffffffffu, asf(up ? pk[4 * g + 1] : pk[4 * g + 3]), 16);
    asm volatile("st.shared.v2.f32 [%0], {%1, %2};"
                 :: "r"(c.sb + OFF_STG + 16384 + (t >> 5) * 768 + g * 256 + (t & 15) * 16 + (t & 16) / 2), "f"(a), "f"(b) : "memory");
  }
  mbar_arrive_warp(c.sb + B_DUMP);
  mbar_spin(c.sb + B_EPOCH, 0);
}
__device__ __forceinline__ void cs_publish(const Cons& c, uint32_t tile) {
  const int t = min(fresh_tid(), 191);
  mbar_spin(c.sb + B_DUMP, 0);
  float v[8];
#pragma unroll
  for (int g = 0; g < 8; g++) v[g] = asf(lds32(c.sb + OFF_STG + 16384 + g * 768 + t * 4));
  st_gpu32_if(t_mp(tile) < 4, g_csp + (t_idx(tile) * 8 + (t_mp(tile) & 3) * 2 + c.rank) * 192 + t,
              tagged(((v[0] + v[1]) + (v[2] + v[3])) + ((v[4] + v[5]) + (v[6] + v[7])), lds32(c.sb + M_EPOCH)));
}

__device__ __forceinline__ void cs_fetch(uint32_t (&cs)[8], uint32_t tile) {
  const uint32_t* part = g_csp + t_idx(tile) * (8 * 192) + min(fresh_tid(), 191);
#pragma unroll
  for (int i = 0; i < 8; i++) cs[i] = ld_gpu32<0>(part + i * 192);
}
__device__ __forceinline__ void cs_finish(const Cons& c, uint32_t (&cs)[8], uint32_t tile, uint32_t tag) {
  while (true) {
    uint32_t bad = 0;
#pragma unroll
    for (int i = 0; i < 8; i++) bad |= cs[i] ^ tag;
    if (!__any_sync(0xffffffffu, (bad & 255) != 0)) break;
    cs_fetch(cs, tile);
  }
  const float sum = ((untagged(cs[0]) + untagged(cs[1])) + (untagged(cs[2]) + untagged(cs[3]))) + ((untagged(cs[4]) + untagged(cs[5])) + (untagged(cs[6]) + untagged(cs[7])));
  const uint32_t h = pack2(sum, sum), col = min(fresh_tid(), 191);
  asm volatile("st.shared.u16 [%0], %1;\nst.shared.u16 [%0 + 16], %2;"
               :: "r"(c.sb + M_CS + (col >> 3) * 32 + (col & 7) * 2), "h"((uint16_t)h), "h"((uint16_t)pack2(sum - bf_lo(h), 0.f)) : "memory");
  fence_async_smem();
}

template <int C>
__device__ __forceinline__ void g_chunk(Cons& c, uint32_t (&pk)[64], float (&ev)[8]) {
  constexpr float C0 = 0.7978845608028654f, C1 = 0.044715f * 0.7978845608028654f;
  if ((C & 3) == 0) out_acquire(c, C >> 2);
  uint32_t o[4];
#pragma unroll
  for (int i = 0; i < 4; i++) {
    const float rs = ev[i & 1];
    const float k0 = C0 * rs, k1 = C1 * rs * rs * rs, k2 = 0.5f * rs * rs;
    const float g0 = bf_lo(pk[4 * C + i]), g1 = bf_hi(pk[4 * C + i]);
    const float t0 = tanh_hw(g0 * fmaf(g0 * g0, k1, k0)), t1 = tanh_hw(g1 * fmaf(g1 * g1, k1, k0));
    o[i] = mul2(pack2(g0 * fmaf(t0, k2, k2), g1 * fmaf(t1, k2, k2)), pk[32 + 4 * C + i]);
  }
  stsm4(srow<(C & 3) * 2>(c) + (C >> 2) * 8192, o[0], o[1], o[2], o[3]);
  if ((C & 3) == 3) out_publish(c, C >> 2);
}

template <int C>
__device__ __forceinline__ void r_chunk(Cons& c, const uint32_t (&pk)[64], const float (&ev)[8]) {
  uint32_t o[16];
#pragma unroll
  for (int i = 0; i < 16; i++) o[i] = add2(pk[16 * C + i], asu(ev[i & 1]));
  out_acquire(c, C & 1);
  stsm4(srow<0>(c) + (C & 1) * 8192, o[0], o[1], o[2], o[3]);
  stsm4(srow<2>(c) + (C & 1) * 8192, o[4], o[5], o[6], o[7]);
  stsm4(srow<4>(c) + (C & 1) * 8192, o[8], o[9], o[10], o[11]);
  stsm4(srow<6>(c) + (C & 1) * 8192, o[12], o[13], o[14], o[15]);
  out_publish(c, C & 1);
}
template <int H>
__device__ __forceinline__ void mma_half(const Cons& c, float (&acc)[64], int i0, int i1) {
#pragma unroll 1
  for (int i = i0; i < i1; i++) {
    const uint32_t s = (c.s + i) & 3;
    if (H == 0) mbar_spin(c.sb + B_FULL + 8 * s, c.ph ^ ((c.s + i) >> 2));
    wg_fence();
    const uint32_t st = ((c.sb & 0x3FFFF) >> 4) + s * (STAGE_BYTES >> 4);
    const uint32_t da = st + c.w * 512 + (1u << 16), db = st + (A_BYTES >> 4) + H * 1024 + (512u << 16);
#pragma unroll
    for (int kk = 0; kk < 4; kk++) wgmma128(acc, desc64(da + kk * 2), desc64(db + kk * 128));
    wg_commit();
  }
}
__device__ __forceinline__ void release_tail(Cons& c, bool hold) {
#pragma unroll 1
  for (int i = 0; i < TAIL; i++) {
    c.prev = hold ? NSTAGE : c.s;
    release_prev(c);
    if (++c.s == NSTAGE) { c.s = 0; c.ph ^= 1; }
  }
  c.prev = NSTAGE;
}
template <int C, bool ADD>
__device__ __forceinline__ void half_out(const Params& p, const Cons& c, const float (&acc)[64], const float (&ev)[8], bool own,
                                         uint32_t mine, int col, int row) {
#pragma unroll
  for (int i = 4 * C; i < 4 * C + 4; i++) {
    uint32_t o[4];
#pragma unroll
    for (int j = 0; j < 4; j++) {
      o[j] = pack2(acc[8 * i + 2 * j], acc[8 * i + 2 * j + 1]);
      if (ADD) o[j] = add2(o[j], asu(ev[j & 1]));
    }
    stsm4((c.srow ^ ((i & 3) << 5)) + C * 8192, o[0], o[1], o[2], o[3]);
  }
  fence_async_smem();
  __syncwarp();
  if (own) tma_add3d(&p.tm[TM_OUT16], mine + C * 8192, col + C * 64, row, 0);
  else mbar_arrive_warp(c.sb + B_OUTF + c.w * 16 + C * 8);
  sched_fence(c.sb);
}

template <int N>
__device__ __forceinline__ void mma_run(Cons& c, float (&acc)[128], int k0, int k1) {
#pragma unroll 1
  for (int k = k0; k < k1; k++) mma_step<N>(c, acc);
}

__device__ __forceinline__ void tile_end(Cons& c) {
  wg_wait<0>();
  release_prev(c);
  c.prev = NSTAGE;
}

__device__ __forceinline__ void stagger_wait(Cons& c) {
  if (c.w == 1) {
    wg_wait<0>();
    release_prev(c);
    c.prev = NSTAGE;
    asm volatile("bar.sync 7, 256;" ::: "memory");
  }
}

struct RowMeans {
  const uint2* src;
  uint2 v[4];
  uint4 x;
};
__device__ __forceinline__ int first_row(const Cons& c, uint32_t tile) {
  const int t = fresh_tid();
  return (t_mp(tile) * 2 + c.rank) * 128 + (t >> 5) * 16 + ((t & 31) >> 2);
}
__device__ __forceinline__ int mean_slot(const Cons& c, uint32_t tile) {
  const int t = fresh_tid();
  return (t & 4) * 128 + (t_mp(tile) * 2 + c.rank) * 32 + (t >> 5) * 4 + (t & 3);
}
__device__ __forceinline__ void row_means_fetch(RowMeans& s) {
#pragma unroll
  for (int i = 0; i < 4; i++) s.v[i] = ld_gpu64<0>(s.src + i * (2 * S_LEN));
}
__device__ __forceinline__ void row_means_load(RowMeans& s, const Cons& c, uint32_t tile) {
  s.src = nullptr;
  s.v[0] = s.v[1] = s.v[2] = s.v[3] = make_uint2(0, 0);
  s.x = make_uint4(0, 0, 0, 0);
  if ((tile >> 22) & 1) {
    const int o = mean_slot(c, tile);
    if (t_type(tile) == 1) {
      s.x = ld_gpu128((const uint4*)(g_xst + 8) + o);
      s.src = (const uint2*)g_pdot + ((fresh_tid() >> 3) & 3) * (S_LEN / 2) + o;
      row_means_fetch(s);
    } else {
      asm volatile("ld.relaxed.gpu.global.u32 %0, [%1];" : "=r"(s.x.x) : "l"(g_hmean + o) : "memory");
    }
  }
}
__device__ __forceinline__ void row_means_finish(RowMeans& s, const Cons& c, uint32_t tile, float (&ev)[8]) {
  ev[0] = ev[1] = 0.f;
  if ((tile >> 22) & 1) {
    uint32_t m = s.x.x;
    if (t_type(tile) == 1) {
      const uint32_t tag = lds32(c.sb + M_EPOCH);
      while (true) {
        uint32_t bad = 0;
#pragma unroll
        for (int i = 0; i < 4; i++) bad |= (s.v[i].x ^ tag) | (s.v[i].y ^ tag);
        if (!__any_sync(0xffffffffu, (bad & 255) != 0)) break;
        row_means_fetch(s);
      }
      float a = (untagged(s.v[0].x) + untagged(s.v[1].x)) + (untagged(s.v[2].x) + untagged(s.v[3].x));
      float b = (untagged(s.v[0].y) + untagged(s.v[1].y)) + (untagged(s.v[2].y) + untagged(s.v[3].y));
      a += __shfl_xor_sync(0xffffffffu, a, 8); b += __shfl_xor_sync(0xffffffffu, b, 8);
      a += __shfl_xor_sync(0xffffffffu, a, 16); b += __shfl_xor_sync(0xffffffffu, b, 16);
      m = pack2(a + asf(s.x.x), b + asf(s.x.z));
      st_gpu64_if(t_idx(tile) == 0 && (fresh_tid() & 24) == 0, g_hmean + mean_slot(c, tile), m, tag);
      m ^= 0x80008000u;
    }
    const int r = (fresh_tid() & 31) >> 2, from = (r & 1) * 4 + (r >> 2), sel = r & 2 ? 0x3232 : 0x1010;
    ev[0] = asf(__byte_perm(__shfl_sync(0xffffffffu, m, from), 0, sel));
    ev[1] = asf(__byte_perm(__shfl_sync(0xffffffffu, m, from + 2), 0, sel));
  }
}

__device__ __forceinline__ void consumer(const Params& p, uint32_t sb, int w, int rank, int pair) {
  Cons c;
  c.sb = sb; c.w = w; c.rank = rank;
  const int t0 = threadIdx.x & 127;
  c.empty_r = __shfl_sync(0xffffffffu, t0 < 2 ? mapa(sb + B_EMPTY, t0 & 1) : 0u, t0 & 31);
  c.srow = __shfl_sync(0xffffffffu, sb + OFF_STG + w * 16384 + ((t0 >> 5) * 16 + (t0 & 15)) * 128 + ((((t0 >> 4) & 1) ^ (t0 & 7)) << 4), t0 & 31);
  c.s = 0; c.ph = 0; c.prev = NSTAGE; c.phb = 0;
  float acc[128];
  uint32_t pk[64];
  float ev[8];
  const uint32_t* sched = p.sched + pair * MAXT;
  int ti = 0;
  uint32_t tile = __shfl_sync(0xffffffffu, sched[0], 0);
  const int g = __shfl_sync(0xffffffffu, (threadIdx.x >> 5) + 1, 0);
  int k;
  uint32_t cs[8];

  mma_step<192, true>(c, acc);
  {
    const int t = fresh_tid(), row = (t_mp(tile) & 1) * 16 + (t >> 4);
    const uint32_t off = sb + A_BYTES + rank * 12288 + row * 128 + ((((t >> 1) ^ row) & 7) << 4) + (t & 1) * 8;
#pragma unroll
    for (int i = 0; i < 12; i++) pk[i] = 0;
#pragma unroll 1
    for (k = 1; k < 12; k++) {
      if ((unsigned)(k - X_STEP) < 2u) mbar_arrive_warp(sb + B_GO + 8 * (k - X_STEP));
      if (k < 9) cs_accumulate(c, pk, off);
      if (k == 9) cs_dump(c, pk);
      if (k == 10) cs_publish(c, tile);
      mma_step<192>(c, acc);
    }
    cs_fetch(cs, tile);
  }
started192:
  {
    const uint32_t next = __shfl_sync(0xffffffffu, sched[ti + 1], 0);
    mma_run<192>(c, acc, k, 13);
    const int t = fresh_tid(), q = t & 3, r = (t & 31) >> 2;
    const uint32_t tag = lds32(sb + M_EPOCH);
    const int base = rank * 1024 + t_mp(tile) * 128 + (t >> 5) * 16;
    const uint2* own = g_xst + base + r;
    const uint4* before = (const uint4*)(g_xst + base) + q + (base & 1023 ? 0 : 4);
    uint2 e0 = ld_gpu64<64>(own), e1 = ld_gpu64<128>(own);
    uint4 kp = ld_gpu128(before);
    mbar_spin(sb + B_OUTE + (g >> 2 ? 16 : 0), (c.phb & 1) ^ 1);
    c.phb ^= 1;
#pragma unroll 1
    for (int i = t_nk(tile) - 13; i > 0; i--) {
      if (i == 2) {
        if (ti == 0) cs_finish(c, cs, tile, tag);
        mbar_arrive_warp(sb + B_CS);
      }
      if (i == 1) stagger_wait(c);
      mma_step<192>(c, acc);
    }
    while (true) {
      if (!__any_sync(0xffffffffu, (((e0.y ^ tag) | (e1.y ^ tag) | (kp.y ^ tag) | (kp.w ^ tag)) & 255) != 0)) break;
      e0 = ld_gpu64<64>(own); e1 = ld_gpu64<128>(own);
      kp = ld_gpu128(before);
    }
    mbar_spin(sb + B_CS, (c.phb >> 2) & 1);
    p1_centre(c, acc, asf(e0.x), asf(e1.x));
    if (w == 0) asm volatile("bar.arrive 7, 256;" ::: "memory");
    e0.y &= ~255u; e1.y &= ~255u;
    ev[0] = asf(e0.y); ev[1] = asf(e1.y);
    ev[2] = asf(kp.y & ~255u); ev[3] = asf(kp.w & ~255u);
    ev[4] = asf(__shfl_sync(0xffffffffu, e0.y, 8 * q)); ev[5] = asf(__shfl_sync(0xffffffffu, e0.y, 8 * q + 4));
    ev[6] = asf(__shfl_sync(0xffffffffu, e1.y, 8 * q)); ev[7] = asf(__shfl_sync(0xffffffffu, e1.y, 8 * q + 4));
    const bool defer = !((tile >> 24) & 1);
    tile_end(c);
    ti++;
    uint32_t lo[24], hi[24];
    p1_park(c, acc, lo, hi, g, tile);
    if (defer) {
      k = DEF_A;
      if (t_type(next)) {
        p1_attention<256>(c, acc, lo, hi, ev, tile);
        tile = next;
        k = DEF_AW;
        goto started;
      }
      p1_attention<192>(c, acc, lo, hi, ev, tile);
      tile = next;
      goto again192;
    }
    p1_attention<0>(c, acc, lo, hi, ev, tile);
    tile = next;
  }
fresh:
  if (tile == TILE_END) goto done;
  k = 1;
  if (t_type(tile) == 0) {
    mma_step<192, true>(c, acc);
  again192:
#pragma unroll
    for (int i = 0; i < 8; i++) cs[i] = 0;
    goto started192;
  }
  mma_step<256, true>(c, acc);
started:
  {
    const uint32_t next = __shfl_sync(0xffffffffu, sched[ti + 1], 0);
    mma_run<256>(c, acc, k, t_nk(tile) - TAIL);
    RowMeans means;
    row_means_load(means, c, tile);
    if (next == TILE_END) c.empty_r = 0;
    const bool geglu = t_type(tile) == 2;
    if (!geglu && ((tile >> 24) & 1)) {
      const bool last = next == TILE_END;
      mbar_spin(sb + (last ? B_GATE : B_COPY), 0);
      out_acquire(c, 0);
      out_acquire(c, 1);
      float left[64], right[64];
      wg_wait<0>();
      release_prev(c);
      c.prev = NSTAGE;
#pragma unroll
      for (int i = 0; i < 64; i++) asm volatile("add.f32 %0, %1, 0f80000000;" : "=f"(left[i]) : "f"(acc[i]));
      if (w == 1) asm volatile("bar.sync 7, 256;" ::: "memory");
      mma_half<0>(c, left, 0, TAIL);
      asm volatile("bar.arrive %0, 256;" :: "r"(7 - w) : "memory");
      row_means_finish(means, c, tile, ev);
      const float m0 = bf_lo(asu(ev[0])), m1 = bf_lo(asu(ev[1]));
#pragma unroll
      for (int i = 0; i < 64; i++) asm volatile("add.f32 %0, %1, %2;" : "=f"(right[i]) : "f"(acc[64 + i]), "f"(i & 2 ? m1 : m0));
      const int col = t_idx(tile) * 256, row = (t_mp(tile) * 2 + rank) * 128 + (g - 1) * 16;
      const uint32_t mine = sb + OFF_STG + w * 8192 + (g - 1) * 2048;
      wg_wait<0>();
      half_out<0, true>(p, c, left, ev, true, mine, col, row);
      asm volatile("bar.sync %0, 256;" :: "r"(6 - w) : "memory");
      mma_half<1>(c, right, 0, 1);
      sched_fence(sb);
      half_out<1, true>(p, c, left, ev, true, mine, col, row);
      bulk_commit();
      mma_half<1>(c, right, 1, TAIL);
      if (w == 0) asm volatile("bar.arrive 5, 256;" ::: "memory");
      bulk_wait_all();
      mbar_arrive_warp(sb + B_HALF);
      tile_end(c);
      release_tail(c, (tile >> 25) & w);
      const bool own = last || w == 0;
      half_out<0, false>(p, c, right, ev, own, mine, col + 128, row);
      half_out<1, false>(p, c, right, ev, own, mine, col + 128, row);
      if (own) {
        bulk_commit();
        bulk_wait_all();
        if (last) goto done;
        mbar_arrive_warp(sb + B_OUTF);
        mbar_arrive_warp(sb + B_OUTF + 8);
      }
      ti++;
      tile = next;
      goto fresh;
    }
    uint32_t r0 = 0, r1 = 0;
    if (geglu && !((tile >> 30) & 1)) {
      const uint32_t* hrs = g_hrs + first_row(c, tile);
      r0 = ld_gpu32<0>(hrs); r1 = ld_gpu32<32>(hrs);
    }
#pragma unroll 1
    for (int i = TAIL; i > 0; i--) {
      if (i == 2) stagger_wait(c);
      mma_step<256>(c, acc);
    }
    if (w == 0) asm volatile("bar.arrive 7, 256;" ::: "memory");
    if (!geglu) row_means_finish(means, c, tile, ev);
    const bool defer = !((tile >> 24) & 1);
    const uint32_t parked = tile;
    tile_end(c);
    ti++;
#pragma unroll
    for (int i = 0; i < 64; i++) pk[i] = pack2(acc[2 * i], acc[2 * i + 1]);
    tile = next;
    if (defer) { mma_step<256, true>(c, acc); sched_fence(sb); }
    if (!geglu) {
      r_chunk<0>(c, pk, ev);
#define F(C) mma_step<256>(c, acc); sched_fence(sb); r_chunk<C>(c, pk, ev);
      F(1) F(2) F(3)
#undef F
      k = DEF_R;
      goto started;
    }
    k = DEF_G;
    if ((parked >> 30) & 1) {
      const uint32_t* hrs = g_hrs + first_row(c, parked);
      r0 = ld_gpu32<0>(hrs); r1 = ld_gpu32<32>(hrs);
      if (defer) { mma_step<256>(c, acc); sched_fence(sb); k++; }
    }
    {
      const uint32_t tag = lds32(sb + M_EPOCH);
      while (true) {
        if (!__any_sync(0xffffffffu, (((r0 ^ tag) | (r1 ^ tag)) & 255) != 0)) break;
        const uint32_t* hrs = g_hrs + first_row(c, parked);
        r0 = ld_gpu32<0>(hrs); r1 = ld_gpu32<32>(hrs);
      }
      ev[0] = untagged(r0); ev[1] = untagged(r1);
    }
    g_chunk<0>(c, pk, ev);
#define F(C) if (defer) { mma_step<256>(c, acc); sched_fence(sb); } g_chunk<C>(c, pk, ev);
    F(1) F(2) F(3) F(4) F(5) F(6) F(7)
#undef F
    if (defer) goto started;
    wg_wait<0>();
    goto fresh;
  }
done:;
}

__device__ __forceinline__ uint32_t get_epoch(uint32_t sb) {
  mbar_wait(sb + B_EPOCH, 0);
  return lds32(sb + M_EPOCH);
}
__device__ __forceinline__ bool flag_set(bool seen, const uint32_t* flag, uint32_t target) {
  uint32_t v = target;
  asm volatile("{\n.reg .pred p;\nsetp.eq.u32 p, %2, 0;\n@p ld.acquire.gpu.global.u32 %0, [%1];\n}" : "+r"(v) : "l"(flag), "r"((uint32_t)seen) : "memory");
  return (int32_t)(v - target) >= 0;
}

__device__ __forceinline__ void watcher(const Params& p, uint32_t sb, int pair) {
  const uint32_t* sched = p.sched + pair * MAXT;
  const int l = threadIdx.x & 31;
  const uint32_t target = get_epoch(sb) * 32;
  uint32_t base = 0;
  for (int ti = 1;; ti++) {
    const uint32_t tile = __shfl_sync(0xffffffffu, sched[ti], 0);
    if (tile == TILE_END) break;
    const int ty = t_type(tile);
    if (ty == 0) continue;
    const int n = t_deps(tile, t_nk(tile));
    const uint32_t* flag = g_flags + FL_OUT + ((ty - 1) * 8 + t_mp(tile)) * 32 + (t_k0(tile) >> t_sh(tile)) + l;
    bool ok = l >= n;
    int seen = 0;
    while (true) {
      ok = flag_set(ok, flag, target);
      const int lead = __ffs(~__ballot_sync(0xffffffffu, ok) | 0x80000000u) - 1, now = min(lead, n);
      if (now > seen) {
        asm volatile("{\n.reg .pred p;\nsetp.ne.u32 p, %2, 0;\n@p red.relaxed.cluster.shared::cluster.max.u32 [%0], %1;\n}"
                     :: "r"(mapa(sb + M_DEP, (blockIdx.x ^ l) & 1)), "r"(base + now), "r"((uint32_t)(l < (ty == 3 ? 1 : 2))) : "memory");
        seen = now;
        if (now == n) break;
      } else {
        __nanosleep(FLAG_SLEEP);
      }
    }
    base += n;
  }
}

__device__ __forceinline__ void load_stage(uint32_t bar, uint32_t bytes, uint32_t b, const CUtensorMap* tb, int b0, int b1, int b2,
                                           uint32_t a, const CUtensorMap* ta, int a0, int a1, int a2) {
  asm volatile("{\n.reg .pred p;\nelect.sync _|p, 0xffffffff;\n@p mbarrier.arrive.expect_tx.shared::cta.b64 _, [%0], %1;\n"
               "@p cp.async.bulk.tensor.3d.shared::cluster.global.mbarrier::complete_tx::bytes.multicast::cluster [%2], [%3, {%4, %5, %6}], [%0], %12;\n"
               "@p cp.async.bulk.tensor.3d.shared::cluster.global.mbarrier::complete_tx::bytes [%7], [%8, {%9, %10, %11}], [%0];\n}"
               :: "r"(bar), "r"(bytes), "r"(b), "l"(tb), "r"(b0), "r"(b1), "r"(b2), "r"(a), "l"(ta), "r"(a0), "r"(a1), "r"(a2), "h"((uint16_t)3)
               : "memory");
}

__device__ __forceinline__ void mbar_arrive_if(uint32_t bar) {
  asm volatile("{\n.reg .pred p, q;\nelect.sync _|p, 0xffffffff;\nsetp.ne.and.u32 q, %0, 0, p;\n@q mbarrier.arrive.shared::cta.b64 _, [%0];\n}" :: "r"(bar) : "memory");
}

__device__ __forceinline__ void producer(const Params& p, uint32_t sb, int rank, int pair) {
  const uint32_t* sched = p.sched + pair * MAXT;
  uint32_t n = 1, base = 0;
  mbar_arrive_warp(sb + B_EMPTY);
  for (int ti = 0;; ti++) {
    const uint32_t tile = __shfl_sync(0xffffffffu, sched[ti], 0);
    if (tile == TILE_END) break;
    const int ty = t_type(tile), mp = t_mp(tile), idx = t_idx(tile), nk = t_nk(tile), sh = t_sh(tile);
    const int k0 = ty ? t_k0(tile) : p1_k(mp, 0), kmask = ty ? 63 : 15;
    const CUtensorMap* ta = &p.tm[ty == 0 ? TM_X1 : TM_ATTN_A - 1 + ty];
    const CUtensorMap* tb = &p.tm[ty == 0 ? TM_WQKV : ty == 1 ? TM_WO : ty == 3 ? TM_WD : rank ? TM_WU : TM_WG];
    const int a1 = ty ? (mp * 2 + rank) * 128 : mp * 128, a2 = ty ? 0 : rank;
    const int b0 = ty ? 0 : idx * 64, b1 = ty ? 0 : rank * 32, b2 = ty == 0 ? 0 : ty == 2 ? idx * 2 : idx * 4 + rank * 2;
    const uint32_t boff = A_BYTES + rank * (ty ? 16384 : 12288), bytes = ty ? STAGE_BYTES : 40960;
    if (ty) mbar_wait(sb + B_ROWDONE, 0);
    const bool duty = (tile >> 26) & 1;
    int ka = ti == 0, kb = ka;
    const uint32_t n0 = n - ka;
    while (true) {
      int avail = nk;
      if (ty) {
        uint32_t known;
        asm volatile("ld.acquire.cta.shared.u32 %0, [%1];" : "=r"(known) : "r"(sb + M_DEP) : "memory");
        avail = min(nk, (((k0 >> sh) + (int)(__shfl_sync(0xffffffffu, known, 0) - base)) << sh) - k0);
        fence_async_all();
      }
#pragma unroll 1
      for (; ka < min(kb, avail); ka++) {
        const uint32_t st = (n0 + ka) & 3;
        asm volatile("{\n.reg .pred p;\nelect.sync _|p, 0xffffffff;\n"
                     "@p cp.async.bulk.tensor.3d.shared::cluster.global.mbarrier::complete_tx::bytes [%0], [%1, {%3, %4, %5}], [%2];\n}"
                     :: "r"(sb + st * STAGE_BYTES), "l"(ta), "r"(sb + B_FULL + 8 * st), "r"(((k0 + ka) & kmask) * 64), "r"(a1), "r"(a2) : "memory");
      }
#pragma unroll 1
      for (; kb < avail; n++) {
        const uint32_t st = n & 3, dst = sb + st * STAGE_BYTES;
        const int kc = ((k0 + kb) & kmask) * 64;
        mbar_wait(sb + B_EMPTY + 8 * st, ((n >> 2) & 1) ^ 1);
        load_stage(sb + B_FULL + 8 * st, bytes, dst + boff, tb, b0, kc + b1, b2, dst, ta, kc, a1, a2);
        mbar_arrive_if(!duty ? sb + B_EMPTY + 8 * st : kb == 3 ? sb + B_DUTY : 0u);
        ka = ++kb;
      }
      if (ka == nk) break;
      const uint32_t st = n & 3;
      if (kb < nk && kb - ka < (ka ? NSTAGE - 1 : NSTAGE) && mbar_test(sb + B_EMPTY + 8 * st, ((n >> 2) & 1) ^ 1)) {
        asm volatile("{\n.reg .pred p;\nelect.sync _|p, 0xffffffff;\n@p mbarrier.arrive.expect_tx.shared::cta.b64 _, [%0], %1;\n"
                     "@p cp.async.bulk.tensor.3d.shared::cluster.global.mbarrier::complete_tx::bytes.multicast::cluster [%2], [%3, {%4, %5, %6}], [%0], %7;\n}"
                     :: "r"(sb + B_FULL + 8 * st), "r"(bytes), "r"(sb + st * STAGE_BYTES + boff), "l"(tb), "r"(b0), "r"(((k0 + kb) & kmask) * 64 + b1), "r"(b2),
                        "h"((uint16_t)3) : "memory");
        mbar_arrive_if(!duty ? sb + B_EMPTY + 8 * st : kb == 3 ? sb + B_DUTY : 0u);
        kb++;
        n++;
      } else {
        __nanosleep(20);
      }
    }
    if (ty) base += t_deps(tile, nk);
  }
}

template <int PITCH>
__device__ __forceinline__ void rows_g2s(uint32_t dst, const void* src, uint32_t bar) {
  asm volatile("{\n.reg .pred p;\nelect.sync _|p, 0xffffffff;\n@p mbarrier.arrive.expect_tx.shared::cta.b64 _, [%2], 8192;\n"
               "@p cp.async.bulk.shared::cluster.global.mbarrier::complete_tx::bytes [%0], [%1], 2048, [%2];\n"
               "@p cp.async.bulk.shared::cluster.global.mbarrier::complete_tx::bytes [%0 + 2048], [%1 + %3], 2048, [%2];\n"
               "@p cp.async.bulk.shared::cluster.global.mbarrier::complete_tx::bytes [%0 + 4096], [%1 + %4], 2048, [%2];\n"
               "@p cp.async.bulk.shared::cluster.global.mbarrier::complete_tx::bytes [%0 + 6144], [%1 + %5], 2048, [%2];\n}"
               :: "r"(dst), "l"(src), "r"(bar), "n"(PITCH), "n"(2 * PITCH), "n"(3 * PITCH) : "memory");
}
__device__ __forceinline__ void sum_sq8(const uint4& v, float& s, float& qq) {
  const float a0 = bf_lo(v.x), b0 = bf_hi(v.x), a1 = bf_lo(v.y), b1 = bf_hi(v.y), a2 = bf_lo(v.z), b2 = bf_hi(v.z), a3 = bf_lo(v.w), b3 = bf_hi(v.w);
  s += ((a0 + b0) + (a1 + b1)) + ((a2 + b2) + (a3 + b3));
  qq += fmaf(a0, a0, fmaf(b0, b0, fmaf(a1, a1, b1 * b1))) + fmaf(a2, a2, fmaf(b2, b2, fmaf(a3, a3, b3 * b3)));
}
__device__ __forceinline__ float inv_std(float s, float qq) {
  const float mu = s * (1.f / DM);
  return rsqrtf(fmaxf(qq * (1.f / DM) - mu * mu, 0.f) + 1e-5f);
}

__device__ __forceinline__ void x_rows(const Params& p, uint32_t sb, int w) {
  const int l = threadIdx.x & 31;
  if (blockIdx.x < 128) {
    const int row0 = blockIdx.x * 8 + w;
    const uint32_t bar = sb + B_ROW + 16 * w;
    uint32_t reg = sb + (2 * w + 1) * STAGE_BYTES - 8192;
    mbar_wait(sb + B_GO, 0);
    rows_g2s<4096>(reg, p.x + (size_t)row0 * DM, bar);
    const uint32_t tag = get_epoch(sb);
#pragma unroll 1
    for (int pass = 0; pass < 2; pass++) {
      mbar_wait(bar + 8 * pass, 0);
      float s = 0.f, qq = 0.f;
      const uint32_t src = reg + (l >> 3) * 2048 + (l & 7) * 16;
#pragma unroll 1
      for (int u = 0; u < 2048; u += 512) {
        if (pass == 0 && u == 1024) rows_g2s<4096>(reg + STAGE_BYTES, p.x + (size_t)(1024 + row0) * DM, bar + 8);
        uint4 v[4];
#pragma unroll
        for (int i = 0; i < 4; i++) v[i] = lds128(src + u + i * 128);
        sched_fence(sb);
#pragma unroll
        for (int i = 0; i < 4; i++) sum_sq8(v[i], s, qq);
      }
#pragma unroll
      for (int o = 1; o < 8; o <<= 1) { s += __shfl_xor_sync(0xffffffffu, s, o); qq += __shfl_xor_sync(0xffffffffu, qq, o); }
      const int o = w * 1024 + pass * 512 + blockIdx.x * 4 + (l >> 3);
      st_gpu64_if((l & 7) == 0, g_xst + 8 + o, asu(s * (1.f / DM)), tagged(inv_std(s, qq), tag));
#pragma unroll 1
      for (int i = 0; i < 4; i++) {
        asm volatile("{\n.reg .pred p;\nelect.sync _|p, 0xffffffff;\n@p cp.async.bulk.global.shared::cta.bulk_group [%0], [%1], 2048;\n}"
                     :: "l"(p.out + (size_t)(pass * 1024 + row0 + 2 * i) * DM), "r"(reg + i * 2048) : "memory");
        bulk_commit();
        bulk_wait_read<0>();
      }
      reg += STAGE_BYTES;
    }
    bulk_wait_all();
  }
  __syncwarp();
  asm volatile("{\n.reg .pred p;\nsetp.lt.u32 p, %1, 2;\n@p mbarrier.arrive.shared::cluster.b64 _, [%0];\n}"
               :: "r"(mapa(sb + B_ROWDONE, l & 1)), "r"(l) : "memory");
}

__device__ __forceinline__ void wo_rows(const Params& p, uint32_t sb, uint32_t tag) {
  const int l = threadIdx.x & 31, row = l >> 2;
  mbar_wait(sb + B_GO + 8, 0);
  rows_g2s<2048>(sb + OFF_STG + 8192, p.wo + (size_t)blockIdx.x * 8 * DM, sb + B_ROW + 32);
  rows_g2s<2048>(sb + OFF_STG + 24576, p.wo + (size_t)(blockIdx.x * 8 + 4) * DM, sb + B_ROW + 32);
  mbar_wait(sb + B_ROW + 32, 0);
  const uint32_t src = sb + OFF_STG + 8192 + (row >> 2) * 16384 + (row & 3) * 2048 + (row & 1) * 64 + (l & 3) * 16;
  float s = 0.f;
#pragma unroll 1
  for (int u = 0; u < 2048; u += 256) {
    const uint4 v[4] = {lds128(src + u), lds128((src ^ 64) + u), lds128(src + u + 128), lds128((src ^ 64) + u + 128)};
    sched_fence(sb);
#pragma unroll
    for (int i = 0; i < 4; i++) {
      const uint32_t a = add2(v[i].x, v[i].y), b = add2(v[i].z, v[i].w);
      s += (bf_lo(a) + bf_hi(a)) + (bf_lo(b) + bf_hi(b));
    }
  }
  s = quad_sum(s);
  st_gpu64_if((l & 3) == 0, g_rm + blockIdx.x * 8 + row, asu(s * (1.f / DM)), tag);
}

__device__ __forceinline__ void aux_warp(const Params& p, uint32_t sb, int rank, int pair) {
  const int l = threadIdx.x & 31;
  const uint32_t ep = get_epoch(sb);
  mbar_wait(sb + B_ROWDONE, 0);
  if (blockIdx.x < 128) flag_add(l ? nullptr : g_flags + FL_COPY, 1);
  while (true) {
    if (__all_sync(0xffffffffu, flag_set(false, g_flags + FL_COPY, ep * 128))) break;
    __nanosleep(200);
  }
  fence_async_all();
  mbar_arrive_warp(sb + B_COPY);
  const uint32_t* sched = p.sched + pair * MAXT;
  uint32_t n = 0, ph = 0;
  for (int ti = 0;; ti++) {
    const uint32_t tile = __shfl_sync(0xffffffffu, sched[ti], 0);
    if (tile == TILE_END) break;
    if ((tile >> 26) & 1) {
      const int wide = (tile >> 23) & 1, row = ((tile >> 27) & 7) * 16 + (l >> (1 - wide));
      const uint32_t src = sb + row * 128, half = wide ? (row >> 2) & 1 : l & 1;
      float s = 0.f, qq = 0.f;
      mbar_wait(sb + B_DUTY, ph);
      ph ^= 1;
#pragma unroll 1
      for (uint32_t k = n; k < n + 16; k++) {
        const uint32_t st = k & 3;
        mbar_wait(sb + B_FULL + 8 * st, (k >> 2) & 1);
#pragma unroll 1
        for (int j = wide; j >= 0; j--) {
          uint4 v[4];
#pragma unroll
          for (int i = 0; i < 4; i++) v[i] = lds128(src + st * STAGE_BYTES + (half ^ j) * 64 + (((i + row) & 3) << 4));
          mbar_arrive_if(j ? 0u : sb + B_EMPTY + 8 * st);
#pragma unroll
          for (int i = 0; i < 4; i++) {
            const uint32_t t = fma2(v[i].w, v[i].w, fma2(v[i].z, v[i].z, fma2(v[i].y, v[i].y, mul2(v[i].x, v[i].x))));
            s += bf_lo(t); qq += bf_hi(t);
          }
        }
      }
      qq += s;
      if (!wide) qq += __shfl_xor_sync(0xffffffffu, qq, 1);
      st_gpu32_if(wide || !(l & 1), g_hrs + (t_mp(tile) * 2 + rank) * 128 + row, tagged(inv_std(0.f, qq), ep));
    }
    n += t_nk(tile);
  }
}

__device__ __forceinline__ void io_warp(const Params& p, uint32_t sb, int rank, int pair) {
  const uint32_t* sched = p.sched + pair * MAXT;
  const int l = threadIdx.x & 31;
  uint32_t phb = 0;
  uint32_t steps = 0;
  const uint32_t ep = get_epoch(sb);
  if (blockIdx.x < 128) wo_rows(p, sb, ep);
  for (int ti = 0;; ti++) {
    const uint32_t tile = __shfl_sync(0xffffffffu, sched[ti], 0);
    if (tile == TILE_END) break;
    const int ty = t_type(tile), mp = t_mp(tile), idx = t_idx(tile);
    if (ty == 0) {
      if (ti == 0) {
        const uint4* src = (const uint4*)(g_rm + idx * 64) + l;
        uint4 e;
        while (true) {
          e = ld_gpu128(src);
          if (!__any_sync(0xffffffffu, e.y != ep || e.w != ep)) break;
          __nanosleep(100);
        }
        const uint32_t dst = sb + M_RM + (l >> 4) * 128 + (l & 3) * 32 + ((l >> 2) & 3) * 4;
        asm volatile("st.shared.u32 [%0], %1;\nst.shared.u32 [%0 + 16], %2;" :: "r"(dst), "r"(e.x), "r"(e.z) : "memory");
        mbar_arrive_warp(sb + B_RM);
      }
      uint4* box = g_halo + ((mp * 2 - 2 + rank) * 16 + idx) * 128 + l;
      uint4 v[4];
#pragma unroll
      for (int i = 0; i < 4; i++) v[i] = make_uint4(~0u, ~0u, ~0u, ~0u);
      if (mp) {
        while (true) {
          uint32_t least = ~0u;
#pragma unroll
          for (int i = 0; i < 4; i++) v[i] = ld_gpu128(box + i * 32);
#pragma unroll
          for (int i = 0; i < 4; i++) least = min(min(least, min(v[i].x, v[i].y)), min(v[i].z, v[i].w));
          if (!__any_sync(0xffffffffu, least == 0)) break;
          mbar_wait(sb + B_CS, (phb >> 2) & 1);
        }
      }
      phb ^= 4;
#pragma unroll
      for (int i = 0; i < 4; i++) stsm4(sb + OFF_STG + i * 512 + l * 16, ~v[i].x, ~v[i].y, ~v[i].z, ~v[i].w);
      mbar_arrive_warp(sb + B_HALO);
#pragma unroll
      for (int i = 0; i < 4; i++) st_gpu128_if(mp, box + i * 32, 0u, 0u, 0u, 0u);
    } else if (ty == 1) {
      mbar_wait(sb + B_COPY, 0);
    } else if (ty == 3) {
      const uint32_t* flag = g_flags + FL_OUT + (16 + mp) * 32 + l;
      bool ok = l >= 28;
      while (true) {
        ok = flag_set(ok, flag, ep * 32);
        if (__all_sync(0xffffffffu, ok)) break;
        __nanosleep(FLAG_SLEEP);
      }
      fence_async_all();
      if (sched[ti + 1] == TILE_END) {
        mbar_arrive_warp(sb + B_GATE);
        break;
      }
    }
    const int split = (tile >> 24) & ty & 1;
    const bool early = (tile >> 25) & 1;
    const int n = ty == 0 ? 2 : ty == 2 ? 4 : 8, col0 = idx * (n * 32), row0 = ty == 0 ? mp * 128 : (mp * 2 + rank) * 128;
    uint32_t* done = g_flags + FL_OUT + (ty * 8 + mp) * 32 + (ty == 1 ? idx * 2 + 1 : idx);
    const CUtensorMap* tm = &p.tm[ty == 0 ? TM_ATTN_ST : ty == 2 ? TM_ACT_ST : TM_OUT_ST];
    uint32_t before = 0;
    steps += t_nk(tile);
    if (split) {
      mbar_wait(sb + B_HALF, (phb >> 3) & 1);
      phb ^= 8 + 3;
      if (early) flag_add(l ? nullptr : done - 1, t_nk(tile));
    }
#pragma unroll 1
    for (int i = split * 5; i < n; i += 1 + split) {
      const int w = i & 1, ch = i >> 1, sub = ch & 1;
      mbar_wait(sb + B_OUTF + w * 16 + sub * 8, ((phb >> sub) ^ (i >> 2)) & 1);
      const uint32_t src = sb + OFF_STG + w * 16384 + sub * 8192;
      if (ty & 1) tma_add3d(tm, src, col0 + ch * 64, row0 + w * 64, 0);
      else tma_st3d(tm, src, col0 + ch * 64, row0 + w * 64, ty == 0 ? rank : 0);
      bulk_commit();
      bulk_wait_read<1>();
      if (before) mbar_arrive_warp(before);
      before = sb + B_OUTE + w * 16 + sub * 8;
    }
    if (split) {
      mbar_wait(sb + B_OUTF + 8, ((phb >> 1) & 1) ^ 1);
      mbar_arrive_warp(sb + B_OUTE);
      mbar_arrive_warp(sb + B_OUTE + 8);
    }
    phb ^= n == 2 ? 1 : n == 4 ? 3 : 0;
    bulk_wait_all();
    mbar_arrive_warp(before);
    if (ty != 3) flag_add(l == 0 ? done : ty == 1 && l == 1 && !early ? done - 1 : nullptr, t_nk(tile));
    asm volatile("{\n.reg .pred p;\nsetp.ne.u32 p, %1, 0;\n@p mbarrier.arrive.shared::cluster.b64 _, [%0];\n}"
                 :: "r"(mapa(sb + B_EMPTY + 8 * ((steps + 1 + (l >> 1)) & 3), l & 1)), "r"((uint32_t)(early && l < 2 * TAIL)) : "memory");
  }
}

__global__ void __cluster_dims__(2, 1, 1) __launch_bounds__(384, 1) fused_block_kernel(const __grid_constant__ Params p) {
  extern __shared__ __align__(1024) uint8_t smem_raw[];
  uint32_t sb = (uint32_t)__cvta_generic_to_shared(smem_raw);
  asm volatile("" : "+r"(sb));
  sb = __shfl_sync(0xffffffffu, sb, 0);
  const int wg = __shfl_sync(0xffffffffu, threadIdx.x >> 7, 0);
  const int rank = __shfl_sync(0xffffffffu, blockIdx.x & 1, 0), pair = __shfl_sync(0xffffffffu, blockIdx.x >> 1, 0);
  const int warp = __shfl_sync(0xffffffffu, threadIdx.x >> 5, 0) - 8;
  if (warp == 0) {
    const uint32_t t0 = (pair >> 4) << 2 | (pair & 15) << 5;
    const int kc = p1_k(t_mp(t0), 0) * 64;
    asm volatile("{\n.reg .pred p;\nelect.sync _|p, 0xffffffff;\n"
                 "@p mbarrier.init.shared::cta.b64 [%0], 1;\nfence.mbarrier_init.release.cluster;\nfence.proxy.async.shared::cta;\n"
                 "@p mbarrier.arrive.expect_tx.shared::cta.b64 _, [%0], 40960;\n"
                 "@p cp.async.bulk.tensor.3d.shared::cluster.global.mbarrier::complete_tx::bytes [%1 + 16384], [%2, {%4, %5, %9}], [%0];\n"
                 "@p cp.async.bulk.tensor.3d.shared::cluster.global.mbarrier::complete_tx::bytes [%1], [%3, {%5, %7, %8}], [%0];\n"
                 "@p cp.async.bulk.tensor.3d.shared::cluster.global.mbarrier::complete_tx::bytes [%1 + 28672], [%2, {%4, %6, %9}], [%0];\n}"
                 :: "r"(sb + B_FULL), "r"(sb), "l"(&p.tm[TM_WQKV]), "l"(&p.tm[TM_X1]), "r"(t_idx(t0) * 64), "r"(kc), "r"(kc + 32),
                    "r"(t_mp(t0) * 128), "r"(rank), "r"(0) : "memory");
  }
  if (threadIdx.x == 0) {
#pragma unroll
    for (int i = 0; i < 4; i++) {
      if (i) mbar_init(sb + B_FULL + 8 * i, 1);
      mbar_init(sb + B_EMPTY + 8 * i, 5); mbar_init(sb + B_OUTF + 8 * i, 4); mbar_init(sb + B_OUTE + 8 * i, 1); mbar_init(sb + B_ROW + 8 * i, 1);
    }
    mbar_init(sb + B_HALO, 4); mbar_init(sb + B_HALO + 8, 4); mbar_init(sb + B_RM, 1); mbar_init(sb + B_EPOCH, 1);
    mbar_init(sb + B_CS, 8); mbar_init(sb + B_ROWDONE, 4); mbar_init(sb + B_ROW + 32, 2); mbar_init(sb + B_GATE, 1); mbar_init(sb + B_COPY, 1); mbar_init(sb + B_DUMP, 8); mbar_init(sb + B_HALF, 8);
    mbar_init(sb + B_GO, 8); mbar_init(sb + B_GO + 8, 8); mbar_init(sb + B_DUTY, 1);
    asm volatile("st.shared.u32 [%0], %1;" :: "r"(sb + M_DEP), "r"(0) : "memory");
    asm volatile("fence.mbarrier_init.release.cluster;" ::: "memory");
    fence_async_smem();
  }
  if (threadIdx.x >= 32 && threadIdx.x < 56) asm volatile("st.shared.u32 [%0], %1;" :: "r"(sb + M_CS + 640 + threadIdx.x * 4), "r"(0) : "memory");
  __syncthreads();
  asm volatile("barrier.cluster.arrive.relaxed.aligned;\nbarrier.cluster.wait.aligned;" ::: "memory");
  if (wg < 2) {
    asm volatile("setmaxnreg.inc.sync.aligned.u32 224;");
    consumer(p, sb, wg, rank, pair);
  } else {
    asm volatile("setmaxnreg.dec.sync.aligned.u32 56;");
    if (warp > 0) {
      if (threadIdx.x == 289) {
        const uint32_t e = atomicAdd(g_flags + FL_LAUNCH, 1u) / (uint32_t)p.ncta + 1;
        asm volatile("st.shared.u32 [%0], %1;" :: "r"(sb + M_EPOCH), "r"(e) : "memory");
        mbar_arrive(sb + B_EPOCH);
#pragma unroll
        for (int i = TM_ATTN_ST; i < TM_COUNT; i++) asm volatile("prefetch.tensormap [%0];" :: "l"(&p.tm[i]) : "memory");
      }
      __syncwarp();
      if (warp == 1) {
        io_warp(p, sb, rank, pair);
      } else {
        x_rows(p, sb, warp - 2);
        if (warp == 2) aux_warp(p, sb, rank, pair);
        else watcher(p, sb, pair);
      }
    } else {
      producer(p, sb, rank, pair);
    }
  }
}

typedef CUresult (*EncodeFn)(CUtensorMap*, CUtensorMapDataType, cuuint32_t, void*, const cuuint64_t*, const cuuint64_t*, const cuuint32_t*,
                             const cuuint32_t*, CUtensorMapInterleave, CUtensorMapSwizzle, CUtensorMapL2promotion, CUtensorMapFloatOOBfill);

void encode(EncodeFn fn, CUtensorMap* m, const void* ptr, uint64_t d0, uint64_t d1, uint64_t d2, uint64_t s1, uint64_t s2,
            uint32_t b0, uint32_t b1, uint32_t b2) {
  const cuuint64_t dims[3] = {d0, d1, d2}, strides[2] = {s1, s2};
  const cuuint32_t box[3] = {b0, b1, b2}, es[3] = {1, 1, 1};
  fn(m, CU_TENSOR_MAP_DATA_TYPE_BFLOAT16, 3, (void*)ptr, dims, strides, box, es, CU_TENSOR_MAP_INTERLEAVE_NONE,
     CU_TENSOR_MAP_SWIZZLE_128B, CU_TENSOR_MAP_L2_PROMOTION_L2_128B, CU_TENSOR_MAP_FLOAT_OOB_FILL_NONE);
}

const uint32_t kSchedule[MAXPAIRS * MAXT] = {
  0x01100000, 0x0110001c, 0x00500051, 0x011002c6, 0x7490001e, 0x0010031e, 0x004d6417, 0x010a5c07, TILE_END, TILE_END, TILE_END, TILE_END, TILE_END, TILE_END, TILE_END, TILE_END,
  0x01100020, 0x0010003c, 0x40100062, 0x401000ee, 0x74100092, 0x00100176, 0x01190017, TILE_END, TILE_END, TILE_END, TILE_END, TILE_END, TILE_END, TILE_END, TILE_END, TILE_END,
  0x01100040, 0x0010005c, 0x7c100102, 0x4010032e, 0x6c100216, 0x00100116, 0x011a006b, TILE_END, TILE_END, TILE_END, TILE_END, TILE_END, TILE_END, TILE_END, TILE_END, TILE_END,
  0x01100060, 0x0010007c, 0x40100142, 0x401000ae, 0x6c100232, 0x001001be, 0x011a0077, TILE_END, TILE_END, TILE_END, TILE_END, TILE_END, TILE_END, TILE_END, TILE_END, TILE_END,
  0x01100080, 0x00100098, 0x40100362, 0x401001ce, 0x40100272, 0x001001de, 0x011a7873, TILE_END, TILE_END, TILE_END, TILE_END, TILE_END, TILE_END, TILE_END, TILE_END, TILE_END,
  0x011000a0, 0x001000bc, 0x401000a2, 0x4010034e, 0x40100236, 0x00558c6f, 0x01158c1f, TILE_END, TILE_END, TILE_END, TILE_END, TILE_END, TILE_END, TILE_END, TILE_END, TILE_END,
  0x011000c0, 0x001000dc, 0x40100162, 0x4010006e, 0x401000b2, 0x004cb02f, 0x015e0073, TILE_END, TILE_END, TILE_END, TILE_END, TILE_END, TILE_END, TILE_END, TILE_END, TILE_END,
  0x011000e0, 0x03042001, 0x54100242, 0x00500079, 0x5c100052, 0x00550043, 0x0156885b, TILE_END, TILE_END, TILE_END, TILE_END, TILE_END, TILE_END, TILE_END, TILE_END, TILE_END,
  0x01100100, 0x01043021, 0x03062805, 0x441000e6, 0x5410002a, 0x0010013e, 0x000c0063, 0x0157001f, TILE_END, TILE_END, TILE_END, TILE_END, TILE_END, TILE_END, TILE_END, TILE_END,
  0x01100120, 0x03470021, 0x00500015, 0x00100346, 0x4010029e, 0x00100312, 0x0156005f, TILE_END, TILE_END, TILE_END, TILE_END, TILE_END, TILE_END, TILE_END, TILE_END, TILE_END,
  0x01100140, 0x00100158, 0x401001e2, 0x4010018e, 0x40100096, 0x001002f2, 0x000d5443, 0x010d541b, TILE_END, TILE_END, TILE_END, TILE_END, TILE_END, TILE_END, TILE_END, TILE_END,
  0x01100160, 0x0010017c, 0x40100342, 0x401001ae, 0x401000d2, 0x001001da, 0x000dac43, 0x010d6837, TILE_END, TILE_END, TILE_END, TILE_END, TILE_END, TILE_END, TILE_END, TILE_END,
  0x01100180, 0x03041001, 0x0146280d, 0x4c100106, 0x5c10004a, 0x4c10027a, 0x0010033a, 0x01129817, TILE_END, TILE_END, TILE_END, TILE_END, TILE_END, TILE_END, TILE_END, TILE_END,
  0x011001a0, 0x001001b8, 0x401002c2, 0x4010004e, 0x401001d6, 0x001000ba, 0x000d686b, 0x010d000f, TILE_END, TILE_END, TILE_END, TILE_END, TILE_END, TILE_END, TILE_END, TILE_END,
  0x011001c0, 0x001001d8, 0x401002e2, 0x4010012e, 0x40100256, 0x001002fa, 0x004c002b, 0x010e0067, TILE_END, TILE_END, TILE_END, TILE_END, TILE_END, TILE_END, TILE_END, TILE_END,
  0x011001e0, 0x034a0005, 0x6c100046, 0x7c10012a, 0x0010027e, 0x000f340f, 0x0114907f, TILE_END, TILE_END, TILE_END, TILE_END, TILE_END, TILE_END, TILE_END, TILE_END, TILE_END,
  0x01100004, 0x014c1061, 0x00500055, 0x00100366, 0x4010025e, 0x0165004f, TILE_END, TILE_END, TILE_END, TILE_END, TILE_END, TILE_END, TILE_END, TILE_END, TILE_END, TILE_END,
  0x01100024, 0x01051c21, 0x01072425, 0x64100006, 0x7410000a, 0x5c10013a, 0x0010033e, 0x0113944f, TILE_END, TILE_END, TILE_END, TILE_END, TILE_END, TILE_END, TILE_END, TILE_END,
  0x01100044, 0x01100054, 0x00500011, 0x00100326, 0x5490023e, 0x0010011e, 0x0158007f, TILE_END, TILE_END, TILE_END, TILE_END, TILE_END, TILE_END, TILE_END, TILE_END, TILE_END,
  0x01100064, 0x01100074, 0x00500071, 0x00100306, 0x4490003e, 0x0010031a, 0x01578407, TILE_END, TILE_END, TILE_END, TILE_END, TILE_END, TILE_END, TILE_END, TILE_END, TILE_END,
  0x01100084, 0x0010009c, 0x40100222, 0x4010020e, 0x401000b6, 0x01290003, TILE_END, TILE_END, TILE_END, TILE_END, TILE_END, TILE_END, TILE_END, TILE_END, TILE_END, TILE_END,
  0x001000a4, 0x001000b8, 0x6c100262, 0x6c10000e, 0x64100036, 0x001002d2, 0x0050a04b, 0x010a5057, TILE_END, TILE_END, TILE_END, TILE_END, TILE_END, TILE_END, TILE_END, TILE_END,
  0x001000c4, 0x011000d0, 0x40100122, 0x4010002e, 0x7c100212, 0x00100136, 0x011a0027, TILE_END, TILE_END, TILE_END, TILE_END, TILE_END, TILE_END, TILE_END, TILE_END, TILE_END,
  0x001000e4, 0x011000f0, 0x0105000d, 0x74100126, 0x4010014a, 0x0010007e, 0x00100332, 0x0153943f, TILE_END, TILE_END, TILE_END, TILE_END, TILE_END, TILE_END, TILE_END, TILE_END,
  0x00100104, 0x00100118, 0x0008002d, 0x40100166, 0x4010016a, 0x001000f2, 0x0123302b, TILE_END, TILE_END, TILE_END, TILE_END, TILE_END, TILE_END, TILE_END, TILE_END, TILE_END,
  0x00100124, 0x00100134, 0x0110013c, 0x00100266, 0x44100012, 0x00100356, 0x0110021a, 0x010cb00f, TILE_END, TILE_END, TILE_END, TILE_END, TILE_END, TILE_END, TILE_END, TILE_END,
  0x01100144, 0x0010015c, 0x40100202, 0x401001ee, 0x40100316, 0x001000da, 0x000d004b, 0x010c607f, TILE_END, TILE_END, TILE_END, TILE_END, TILE_END, TILE_END, TILE_END, TILE_END,
  0x00100164, 0x00100178, 0x40100182, 0x7c1002ae, 0x741002b6, 0x00100156, 0x011a0023, TILE_END, TILE_END, TILE_END, TILE_END, TILE_END, TILE_END, TILE_END, TILE_END, TILE_END,
  0x00100184, 0x00100190, 0x00080009, 0x7c1001c6, 0x401001ea, 0x6410023a, 0x00100352, 0x0153943b, TILE_END, TILE_END, TILE_END, TILE_END, TILE_END, TILE_END, TILE_END, TILE_END,
  0x001001a4, 0x001001b0, 0x001001bc, 0x0050003d, 0x0010024a, 0x001002ba, 0x015e6823, TILE_END, TILE_END, TILE_END, TILE_END, TILE_END, TILE_END, TILE_END, TILE_END, TILE_END,
  0x011001c4, 0x03443001, 0x441000c2, 0x4c1002ce, 0x4c100016, 0x00583063, 0x0113007b, TILE_END, TILE_END, TILE_END, TILE_END, TILE_END, TILE_END, TILE_END, TILE_END, TILE_END,
  0x001001e4, 0x001001f4, 0x001001fc, 0x0050005d, 0x0010032a, 0x001002b2, 0x011000fa, 0x010c5c1f, TILE_END, TILE_END, TILE_END, TILE_END, TILE_END, TILE_END, TILE_END, TILE_END,
  0x00100008, 0x01100014, 0x401002a2, 0x4010028e, 0x40100072, 0x001001ba, 0x00519c37, 0x0109002f, TILE_END, TILE_END, TILE_END, TILE_END, TILE_END, TILE_END, TILE_END, TILE_END,
  0x00100028, 0x00100038, 0x00500069, 0x4410022e, 0x44100276, 0x00100376, 0x00529877, 0x01098843, TILE_END, TILE_END, TILE_END, TILE_END, TILE_END, TILE_END, TILE_END, TILE_END,
  0x00100048, 0x00100058, 0x401001c2, 0x4010014e, 0x40100252, 0x00149063, 0x0156881b, TILE_END, TILE_END, TILE_END, TILE_END, TILE_END, TILE_END, TILE_END, TILE_END, TILE_END,
  0x00100068, 0x01100070, 0x40100302, 0x4010036e, 0x401002d6, 0x00100152, 0x011a0037, TILE_END, TILE_END, TILE_END, TILE_END, TILE_END, TILE_END, TILE_END, TILE_END, TILE_END,
  0x00100088, 0x01100094, 0x00500031, 0x011002e6, 0x6490017e, 0x00100172, 0x01170007, TILE_END, TILE_END, TILE_END, TILE_END, TILE_END, TILE_END, TILE_END, TILE_END, TILE_END,
  0x001000a8, 0x001000b4, 0x0008006d, 0x40100146, 0x4010026a, 0x7410015a, 0x004fa403, 0x01140057, TILE_END, TILE_END, TILE_END, TILE_END, TILE_END, TILE_END, TILE_END, TILE_END,
  0x001000c8, 0x001000d4, 0x00482009, 0x401000c6, 0x4010008a, 0x00100292, 0x0010035e, 0x0112005b, TILE_END, TILE_END, TILE_END, TILE_END, TILE_END, TILE_END, TILE_END, TILE_END,
  0x001000e8, 0x001000f4, 0x011000fc, 0x00100286, 0x0010036a, 0x0010019e, 0x015d0033, TILE_END, TILE_END, TILE_END, TILE_END, TILE_END, TILE_END, TILE_END, TILE_END, TILE_END,
  0x00100108, 0x00100110, 0x0048204d, 0x401000a6, 0x4010006a, 0x7c10001a, 0x0123242f, TILE_END, TILE_END, TILE_END, TILE_END, TILE_END, TILE_END, TILE_END, TILE_END, TILE_END,
  0x00100128, 0x00100130, 0x0048206d, 0x401001e6, 0x401000aa, 0x4010007a, 0x0010037e, 0x0112003b, TILE_END, TILE_END, TILE_END, TILE_END, TILE_END, TILE_END, TILE_END, TILE_END,
  0x00100148, 0x00100150, 0x00482065, 0x40100246, 0x401002ea, 0x4010025a, 0x0010037a, 0x0112003f, TILE_END, TILE_END, TILE_END, TILE_END, TILE_END, TILE_END, TILE_END, TILE_END,
  0x00100168, 0x00100174, 0x01080045, 0x01500019, 0x0010022a, 0x00100112, 0x004c000b, 0x0113483b, TILE_END, TILE_END, TILE_END, TILE_END, TILE_END, TILE_END, TILE_END, TILE_END,
  0x00100188, 0x00100194, 0x00080065, 0x40100086, 0x401001aa, 0x0010015e, 0x0010021e, 0x0153947b, TILE_END, TILE_END, TILE_END, TILE_END, TILE_END, TILE_END, TILE_END, TILE_END,
  0x011001a8, 0x03040001, 0x4c100002, 0x5410024e, 0x541001f6, 0x001000f6, 0x011b7433, TILE_END, TILE_END, TILE_END, TILE_END, TILE_END, TILE_END, TILE_END, TILE_END, TILE_END,
  0x001001c8, 0x001001d0, 0x001001dc, 0x00500059, 0x0010030a, 0x001000be, 0x015e6827, TILE_END, TILE_END, TILE_END, TILE_END, TILE_END, TILE_END, TILE_END, TILE_END, TILE_END,
  0x001001e8, 0x001001f8, 0x00080049, 0x40100066, 0x4010028a, 0x6c10005a, 0x0123300b, TILE_END, TILE_END, TILE_END, TILE_END, TILE_END, TILE_END, TILE_END, TILE_END, TILE_END,
  0x0010000c, 0x00100018, 0x0048202d, 0x401001a6, 0x4010018a, 0x4010017a, 0x0010035a, 0x01132853, TILE_END, TILE_END, TILE_END, TILE_END, TILE_END, TILE_END, TILE_END, TILE_END,
  0x0010002c, 0x01100034, 0x401001a2, 0x4010010e, 0x40100076, 0x001002fe, 0x015a7857, TILE_END, TILE_END, TILE_END, TILE_END, TILE_END, TILE_END, TILE_END, TILE_END, TILE_END,
  0x0010004c, 0x01100050, 0x01040061, 0x00500075, 0x441000ea, 0x0010005e, 0x001001fe, 0x0115001b, TILE_END, TILE_END, TILE_END, TILE_END, TILE_END, TILE_END, TILE_END, TILE_END,
  0x0010006c, 0x00100078, 0x40100322, 0x4010016e, 0x401002f6, 0x001000fe, 0x0050700f, 0x010a0053, TILE_END, TILE_END, TILE_END, TILE_END, TILE_END, TILE_END, TILE_END, TILE_END,
  0x0010008c, 0x01100090, 0x40100282, 0x401000ce, 0x401001b6, 0x005a0047, 0x0110485b, TILE_END, TILE_END, TILE_END, TILE_END, TILE_END, TILE_END, TILE_END, TILE_END, TILE_END,
  0x001000ac, 0x011000b0, 0x0105140d, 0x54100026, 0x6c10010a, 0x5410003a, 0x00100192, 0x0113945f, TILE_END, TILE_END, TILE_END, TILE_END, TILE_END, TILE_END, TILE_END, TILE_END,
  0x001000cc, 0x001000d8, 0x641000e2, 0x641002ee, 0x641001f2, 0x00100132, 0x011b7413, TILE_END, TILE_END, TILE_END, TILE_END, TILE_END, TILE_END, TILE_END, TILE_END, TILE_END,
  0x001000ec, 0x001000f8, 0x0008004d, 0x40100186, 0x401001ca, 0x0010009e, 0x0010011a, 0x01124c7b, TILE_END, TILE_END, TILE_END, TILE_END, TILE_END, TILE_END, TILE_END, TILE_END,
  0x0010010c, 0x00100114, 0x0110011c, 0x001002a6, 0x4c100032, 0x0010009a, 0x015d0013, TILE_END, TILE_END, TILE_END, TILE_END, TILE_END, TILE_END, TILE_END, TILE_END, TILE_END,
  0x0010012c, 0x00100138, 0x00482049, 0x40100226, 0x401002ca, 0x00100336, 0x001001b2, 0x0113483f, TILE_END, TILE_END, TILE_END, TILE_END, TILE_END, TILE_END, TILE_END, TILE_END,
  0x0010014c, 0x00100154, 0x01482045, 0x0150001d, 0x0010020a, 0x001000d6, 0x00100372, 0x010f585f, TILE_END, TILE_END, TILE_END, TILE_END, TILE_END, TILE_END, TILE_END, TILE_END,
  0x0010016c, 0x00100170, 0x74100042, 0x7410030e, 0x7c100196, 0x001000de, 0x00519c6b, 0x0109bc0b, TILE_END, TILE_END, TILE_END, TILE_END, TILE_END, TILE_END, TILE_END, TILE_END,
  0x0010018c, 0x00100198, 0x0010019c, 0x00500039, 0x0010034a, 0x0010019a, 0x011e6847, TILE_END, TILE_END, TILE_END, TILE_END, TILE_END, TILE_END, TILE_END, TILE_END, TILE_END,
  0x001001ac, 0x001001b4, 0x5c100022, 0x5c10026e, 0x5c100296, 0x001002da, 0x015b7453, TILE_END, TILE_END, TILE_END, TILE_END, TILE_END, TILE_END, TILE_END, TILE_END, TILE_END,
  0x001001cc, 0x001001d4, 0x40100082, 0x4010008e, 0x40100056, 0x016a3867, TILE_END, TILE_END, TILE_END, TILE_END, TILE_END, TILE_END, TILE_END, TILE_END, TILE_END, TILE_END,
  0x001001ec, 0x001001f0, 0x00500029, 0x0050007d, 0x541001d2, 0x001002de, 0x011b344b, TILE_END, TILE_END, TILE_END, TILE_END, TILE_END, TILE_END, TILE_END, TILE_END, TILE_END,
  0x01100010, 0x00040041, 0x01490025, 0x00500035, 0x4c1000ca, 0x001002be, 0x001001fa, 0x000c6877, 0x0109bc2b, TILE_END, TILE_END, TILE_END, TILE_END, TILE_END, TILE_END, TILE_END,
  0x01100030, 0x034c1041, 0x5c100206, 0x641002aa, 0x4410029a, 0x0123006f, TILE_END, TILE_END, TILE_END, TILE_END, TILE_END, TILE_END, TILE_END, TILE_END, TILE_END, TILE_END,
};

int build_schedule(uint32_t* sched) {
  memcpy(sched, kSchedule, sizeof(kSchedule));
  for (int i = 0; i < MAXPAIRS * MAXT; i++) {
    const uint32_t t = sched[i];
    if (t == TILE_END) continue;
    const uint32_t u = sched[i + 1], ty = t & 3;
    if (u == TILE_END || (ty && !(u & 3)) || (int)((u >> 16) & 63) < (ty == 0 ? DEF_AW : ty == 2 ? DEF_G + ((t >> 30) & 1) : DEF_R) + TAIL) sched[i] |= 1u << 24;
  }
  return MAXPAIRS;
}

}

extern "C" void kernel_launch(void* const* d_in, const int* in_sizes, int n_in, void* d_out, int out_size) {
  static Params p;
  static void* seen[7];
  if (p.out != d_out || memcmp(seen, d_in, sizeof(seen))) {
    memcpy(seen, d_in, sizeof(seen));
    void* fnp = nullptr;
    cudaDriverEntryPointQueryResult qr;
    cudaGetDriverEntryPoint("cuTensorMapEncodeTiled", &fnp, cudaEnableDefault, &qr);
    EncodeFn fn = (EncodeFn)fnp;
    p.x = (const __nv_bfloat16*)d_in[0];
    p.wo = (const __nv_bfloat16*)d_in[2];
    p.out = (__nv_bfloat16*)d_out;
    void *attn, *act;
    cudaGetSymbolAddress(&attn, g_attn);
    cudaGetSymbolAddress(&act, g_act);
    encode(fn, &p.tm[TM_X1], p.x, DM, S_LEN / 2, 2, DM * 4, DM * 2, 64, 128, 1);
    encode(fn, &p.tm[TM_ATTN_ST], attn, DM, S_LEN / 2, 2, DM * 4, DM * 2, 64, 64, 1);
    encode(fn, &p.tm[TM_ATTN_A], attn, DM, S_LEN, 1, DM * 2, S_LEN * DM * 2, 64, 128, 1);
    encode(fn, &p.tm[TM_H_A], d_out, DM, S_LEN, 1, DM * 2, S_LEN * DM * 2, 64, 128, 1);
    encode(fn, &p.tm[TM_ACT_A], act, DF, S_LEN, 1, DF * 2, S_LEN * DF * 2, 64, 128, 1);
    encode(fn, &p.tm[TM_OUT16], d_out, DM, S_LEN, 1, DM * 2, S_LEN * DM * 2, 64, 16, 1);
    encode(fn, &p.tm[TM_OUT_ST], d_out, DM, S_LEN, 1, DM * 2, S_LEN * DM * 2, 64, 64, 1);
    encode(fn, &p.tm[TM_ACT_ST], act, DF, S_LEN, 1, DF * 2, S_LEN * DF * 2, 64, 64, 1);
    encode(fn, &p.tm[TM_WQKV], d_in[1], DM, DM, 3, 3 * DM * 2, DM * 2, 64, 32, 3);
    encode(fn, &p.tm[TM_WO], p.wo, 64, DM, DM / 64, DM * 2, 128, 64, 64, 2);
    encode(fn, &p.tm[TM_WG], d_in[4], 64, DM, DF / 64, DF * 2, 128, 64, 64, 2);
    encode(fn, &p.tm[TM_WU], d_in[5], 64, DM, DF / 64, DF * 2, 128, 64, 64, 2);
    encode(fn, &p.tm[TM_WD], d_in[6], 64, DF, DM / 64, DM * 2, 128, 64, 64, 2);
    cudaFuncSetAttribute(fused_block_kernel, cudaFuncAttributeMaxDynamicSharedMemorySize, SMEM_BYTES);
    p.ncta = 2 * build_schedule(p.sched);
  }
  fused_block_kernel<<<p.ncta, 384, SMEM_BYTES>>>(p);
}
```
